```python
import torch

def _softmax(x, axis=-1):
    return torch.softmax(x, dim=axis)

def _gelu(x):
    return torch.nn.functional.gelu(x, approximate='tanh')

def _silu(x):
    return torch.nn.functional.silu(x)

def _sigmoid(x):
    return torch.sigmoid(x)

def _layernorm(x, axis=-1, eps=1e-05):
    m = x.mean(dim=axis, keepdim=True)
    v = x.var(dim=axis, keepdim=True, unbiased=False)
    return (x - m) / torch.sqrt(v + eps)

def _scatter_add(tgt, idx, src, axis=0):
    return tgt.clone().index_add_(axis, idx, src)

def _segment_sum(src, seg, n):
    out = torch.zeros((n,) + src.shape[1:], dtype=src.dtype)
    return out.index_add_(0, seg, src)

def _pad(x, pw):
    flat = tuple((v for pair in reversed(pw) for v in pair))
    return torch.nn.functional.pad(x, flat)
kernel_name = 'recurrent_scan__memory_aug_recurrent_mem_tr__moe_arch_mod__prompt'

def setup_inputs():

    _w = lambda a: (lambda t: t.to(torch.bfloat16) if t.is_floating_point() else t)(torch.as_tensor(a))

    def _A_setup():
        B, S, Dm = (1, 2048, 640)
        H, Dh = (32, 128)
        M, seg = (8, 32)
        seg = min(seg, S)
        S = S // seg * seg
        return {'x': _w((lambda *s: torch.randn(*s, dtype=torch.bfloat16) * 0.05)(B, S, Dm)), 'mem0': _w((lambda *s: torch.randn(*s, dtype=torch.bfloat16) * 0.2)(B, M, Dm)), 'Wq': _w((lambda *s: torch.randn(*s, dtype=torch.bfloat16) * 1.6)(Dm, H, Dh) * Dm ** (-0.5)), 'Wk': _w((lambda *s: torch.randn(*s, dtype=torch.bfloat16) * 1.6)(Dm, H, Dh) * Dm ** (-0.5)), 'Wv': _w((lambda *s: torch.randn(*s, dtype=torch.bfloat16) * 0.2)(Dm, H, Dh) * Dm ** (-0.5)), 'Wo': _w((lambda *s: torch.randn(*s, dtype=torch.bfloat16) * 0.2)(H, Dh, Dm) * (H * Dh) ** (-0.5)), 'seg_len': seg}
    _A_in = _A_setup()

    def _B_setup():
        B, S, D, F, C = (1, 2048, 640, 1728, 8)
        return {'x': _w((lambda *s: torch.randn(*s, dtype=torch.bfloat16) * 0.05)(B, S, D)), 'w_r': _w((lambda *s: torch.randn(*s, dtype=torch.bfloat16) * 0.2)(D)), 'w_gate': _w((lambda *s: torch.randn(*s, dtype=torch.bfloat16) * 0.1)(D, F)), 'w_up': _w((lambda *s: torch.randn(*s, dtype=torch.bfloat16) * 0.1)(D, F)), 'w_down': _w((lambda *s: torch.randn(*s, dtype=torch.bfloat16) * 0.1)(F, D))}
    _B_in = _B_setup()
    return {'A_x': _A_in['x'], 'A_mem0': _A_in['mem0'], 'A_Wq': _A_in['Wq'], 'A_Wk': _A_in['Wk'], 'A_Wv': _A_in['Wv'], 'A_Wo': _A_in['Wo'], 'A_seg_len': _A_in['seg_len'], 'B_x': _B_in['x'], 'B_w_r': _B_in['w_r'], 'B_w_gate': _B_in['w_gate'], 'B_w_up': _B_in['w_up'], 'B_w_down': _B_in['w_down']}

def reference(A_x, A_mem0, A_Wq, A_Wk, A_Wv, A_Wo, A_seg_len, B_x, B_w_r, B_w_gate, B_w_up, B_w_down):

    def _A_ref(x, mem0, Wq, Wk, Wv, Wo, seg_len):
        B, S, Dm = x.shape
        H, Dh = (Wq.shape[1], Wq.shape[2])
        M = mem0.shape[1]
        scale = Dh ** (-0.5)
        n_seg = S // seg_len
        L = M + seg_len
        idx = torch.arange(L)
        mask = (idx[:, None] < M) | (idx[:, None] >= idx[None, :])
        mem = mem0
        outs = []
        for s in range(n_seg):
            xs = x[:, s * seg_len:(s + 1) * seg_len, :].clone()
            h = torch.concatenate([mem, xs], axis=1)
            q = torch.einsum('btd,dhe->bhte', h, Wq)
            k = torch.einsum('btd,dhe->bhte', h, Wk)
            v = torch.einsum('btd,dhe->bhte', h, Wv)
            scores = torch.einsum('bhqe,bhke->bhqk', q, k) * scale
            scores = torch.where(mask[None, None], scores, -1000000000.0)
            p = _softmax(scores, axis=-1)
            o = torch.einsum('bhqk,bhke->bhqe', p, v)
            o = torch.einsum('bhte,hed->btd', o, Wo)
            mem = o[:, :M, :].clone()
            outs.append(o[:, M:, :])
        return torch.concatenate(outs, axis=1)

    def _B_ref(x, w_r, w_gate, w_up, w_down):
        B, S, D = x.shape
        C = 8
        r = x @ w_r
        idx = torch.argsort(-r, axis=-1)[:, :C]
        idx_e = (lambda x, n, axis: torch.repeat_interleave(x, n, dim=axis))(idx.reshape(B, C, 1), D, axis=2)
        x_sel = (lambda x, i, axis: torch.take_along_dim(x, i, dim=axis))(x, idx_e, axis=1)
        g = _silu(x_sel @ w_gate)
        u = x_sel @ w_up
        y = g * u @ w_down
        r_sel = _sigmoid((lambda x, i, axis: torch.take_along_dim(x, i, dim=axis))(r, idx, axis=1))
        y = y * r_sel.reshape(B, C, 1)
        b_off = (torch.arange(B) * S).reshape(B, 1)
        flat_idx = (idx + b_off).reshape(B * C)
        zero = (x * 0.0).reshape(B * S, D)
        upd = _scatter_add(zero, flat_idx, y.reshape(B * C, D), axis=0)
        return x + upd.reshape(B, S, D)
    x = A_x
    xn = _layernorm(x, axis=-1)
    s = _A_ref(xn, A_mem0, A_Wq, A_Wk, A_Wv, A_Wo, A_seg_len)
    g = _silu(_B_ref(xn, B_w_r, B_w_gate, B_w_up, B_w_down))
    return x + s * g
```

```cpp
#include <cuda_runtime.h>
#include <cuda_bf16.h>
#include <cuda_fp16.h>
#include <stdint.h>
#include <cuda.h>

constexpr int S_TOK = 2048, DM = 640, NH = 32, DH = 128, NSEG = 64, FF = 1728;
constexpr int HD = NH * DH;

#define TRIG 1
#define LN_CTAS 96
#define POLL_DELAY 1030
#define VS_DELAY POLL_DELAY
#define START_DELAY 0
#define MARK_B 0
#define Q_DEPTH 3
#define O_DEPTH 8
#define O_FAST 28
#define LN_WARM 0
#define W_DEPTH 2
#define VS_REGS 208
#define SU 8
#define PVU 4
#define ATT_GATE 6
#define ATT_EAGER 60
#define ATT_REQ 3
#define ATT_H1 4
#define ATT_H2 6
#define ATT_FLAG 7
#define ATT_STAGE 1
#define ATT_START 0
#define ATT_NAP 60
#define PUB_NAP 40
#define KMDUMP(x)
constexpr int PV_UNROLL = PVU, S_UNROLL = SU;
#define SPIN_LIMIT (1 << 20)

__device__ __align__(1024) __nv_bfloat16 g_xn[S_TOK * DM];
__device__ __align__(1024) __half g_xnp[S_TOK * DM];
constexpr int REC_Q = 0, REC_K = 8192, REC_BYTES = 16384;
__device__ __align__(1024) unsigned char g_rec[NH * NSEG * REC_BYTES];
__device__ __align__(1024) uint32_t g_ox[S_TOK * HD / 2];
__device__ __align__(1024) uint4 g_part[6 * 7 * 64 * DM / 8];
__device__ __align__(65536) unsigned char g_ring[2 * 32768];
__host__ __device__ constexpr uint32_t ring_pos(uint32_t p) { return (p & 1) * 256 + (p >> 1) * 1024; }
KMDUMP(__device__ unsigned char g_kmd[NH * NSEG * 4096];)
__device__ float g_r[S_TOK];
__device__ __align__(16) float g_y[27 * 8 * DM];
__device__ __align__(16) float g_yf[8 * DM];
__device__ uint32_t g_epoch;
__device__ __align__(1024) uint32_t g_stamp[8 * 256];
__device__ __align__(8) uint32_t g_fkt[NH * 8];
constexpr int F_LN = 0, F_LN0 = 4, F_W = 5, F_INIT = 8, F_MOD = 16, F_YF = 17, F_XN = 24, F_WV = 25, F_WO = 26, F_Q = 32, F_ATT = 48, F_O = 80, F_EPI = 112, F_WORDS = 144;
__device__ __align__(256) uint32_t g_flags[2][F_WORDS];
#define TS(role, i, dep) do {} while (0)
#define GT(i) do {} while (0)
#define GTM(i) do {} while (0)
#define AT(i) do {} while (0)
#define VT(s, i) do {} while (0)
#define PROF(i) do {} while (0)

__device__ __forceinline__ int tid_now() { int t; asm volatile("mov.u32 %0, %%tid.x;" : "=r"(t)); return t; }
__device__ __forceinline__ uint32_t clk() { uint64_t c; asm volatile("mov.u64 %0, %%clock64;" : "=l"(c) :: "memory"); return (uint32_t)c; }
__device__ __forceinline__ uint32_t gtime_lo() { uint32_t g; asm volatile("mov.u32 %0, %%globaltimer_lo;" : "=r"(g) :: "memory"); return g; }
__device__ __forceinline__ unsigned long long gtime64() { unsigned long long g; asm volatile("mov.u64 %0, %%globaltimer;" : "=l"(g)); return g; }
__device__ __forceinline__ int cta_now() { int t; asm volatile("mov.u32 %0, %%ctaid.x;" : "=r"(t)); return t; }
__device__ __forceinline__ uint32_t smem_u32(const void* p) { return (uint32_t)__cvta_generic_to_shared(p); }
__device__ __forceinline__ uint32_t mapa(uint32_t a, uint32_t r) { uint32_t o; asm("mapa.shared::cluster.u32 %0, %1, %2;" : "=r"(o) : "r"(a), "r"(r)); return o; }
__device__ __forceinline__ void mma16816(float (&c)[4], uint32_t a0, uint32_t a1, uint32_t a2, uint32_t a3, uint32_t b0, uint32_t b1) {
    asm volatile("mma.sync.aligned.m16n8k16.row.col.f32.bf16.bf16.f32 {%0,%1,%2,%3},{%4,%5,%6,%7},{%8,%9},{%0,%1,%2,%3};"
        : "+f"(c[0]), "+f"(c[1]), "+f"(c[2]), "+f"(c[3]) : "r"(a0), "r"(a1), "r"(a2), "r"(a3), "r"(b0), "r"(b1));
}
__device__ __forceinline__ void mma16816(float (&c)[4], const uint4& a, uint32_t b0, uint32_t b1) { mma16816(c, a.x, a.y, a.z, a.w, b0, b1); }
__device__ __forceinline__ void mma16816h(float (&c)[4], const uint4& a, uint32_t b0, uint32_t b1) {
    asm volatile("mma.sync.aligned.m16n8k16.row.col.f32.f16.f16.f32 {%0,%1,%2,%3},{%4,%5,%6,%7},{%8,%9},{%0,%1,%2,%3};"
        : "+f"(c[0]), "+f"(c[1]), "+f"(c[2]), "+f"(c[3]) : "r"(a.x), "r"(a.y), "r"(a.z), "r"(a.w), "r"(b0), "r"(b1));
}
__device__ __forceinline__ void mma1688(float (&c)[4], uint32_t a0, uint32_t a1, uint32_t b0) {
    asm volatile("mma.sync.aligned.m16n8k8.row.col.f32.bf16.bf16.f32 {%0,%1,%2,%3},{%4,%5},{%6},{%0,%1,%2,%3};"
        : "+f"(c[0]), "+f"(c[1]), "+f"(c[2]), "+f"(c[3]) : "r"(a0), "r"(a1), "r"(b0));
}
__device__ __forceinline__ uint32_t movmat(uint32_t a) { uint32_t d; asm volatile("movmatrix.sync.aligned.m8n8.trans.b16 %0, %1;" : "=r"(d) : "r"(a)); return d; }
__device__ __forceinline__ uint32_t pack_bf16(float lo, float hi) { uint32_t d; asm("cvt.rn.bf16x2.f32 %0, %1, %2;" : "=r"(d) : "f"(hi), "f"(lo)); return d; }
__device__ __forceinline__ uint32_t pack_f16(float lo, float hi) { uint32_t d; asm("cvt.rn.f16x2.f32 %0, %1, %2;" : "=r"(d) : "f"(hi), "f"(lo)); return d; }
__device__ __forceinline__ uint32_t bf16x2_to_f16x2(uint32_t w, float sc) {
    const uint32_t s2 = (__float_as_uint(sc) >> 16) | __float_as_uint(sc);
    asm("mul.rn.bf16x2 %0, %0, %1;" : "+r"(w) : "r"(s2));
    return pack_f16(__uint_as_float(w << 16), __uint_as_float(w & 0xffff0000u));
}
__device__ __forceinline__ uint32_t bf16x2_to_f16x2p(uint32_t w, uint32_t s2) {
    asm("mul.rn.bf16x2 %0, %0, %1;" : "+r"(w) : "r"(s2));
    return pack_f16(__uint_as_float(w << 16), __uint_as_float(w & 0xffff0000u));
}
__device__ __forceinline__ int f16_exp(float bound) { return min(max(141 - (int)((__float_as_uint(bound) >> 23) & 255u), -110), 110); }
__device__ __forceinline__ float pow2i(int k) { return __uint_as_float((uint32_t)(127 + k) << 23); }
__device__ __forceinline__ float ex2(float x) { float y; asm("ex2.approx.ftz.f32 %0, %1;" : "=f"(y) : "f"(x)); return y; }
__device__ __forceinline__ uint4 lds128(uint32_t a) { uint4 v; asm volatile("ld.volatile.shared.v4.u32 {%0,%1,%2,%3}, [%4];" : "=r"(v.x), "=r"(v.y), "=r"(v.z), "=r"(v.w) : "r"(a) : "memory"); return v; }
__device__ __forceinline__ uint32_t lds32(uint32_t a) { uint32_t v; asm volatile("ld.volatile.shared.u32 %0, [%1];" : "=r"(v) : "r"(a) : "memory"); return v; }
__device__ __forceinline__ uint2 lds64(uint32_t a) { uint2 v; asm volatile("ld.volatile.shared.v2.u32 {%0,%1}, [%2];" : "=r"(v.x), "=r"(v.y) : "r"(a) : "memory"); return v; }
__device__ __forceinline__ void sts128(uint32_t a, uint32_t x, uint32_t y, uint32_t z, uint32_t w) { asm volatile("st.volatile.shared.v4.u32 [%0], {%1,%2,%3,%4};" :: "r"(a), "r"(x), "r"(y), "r"(z), "r"(w) : "memory"); }
__device__ __forceinline__ void sts128(uint32_t a, const uint4& v) { sts128(a, v.x, v.y, v.z, v.w); }
__device__ __forceinline__ void sts128f(uint32_t a, float x, float y, float z, float w) { sts128(a, __float_as_uint(x), __float_as_uint(y), __float_as_uint(z), __float_as_uint(w)); }
__device__ __forceinline__ void sts64(uint32_t a, uint32_t x, uint32_t y) { asm volatile("st.volatile.shared.v2.u32 [%0], {%1,%2};" :: "r"(a), "r"(x), "r"(y) : "memory"); }
__device__ __forceinline__ void sts32(uint32_t a, uint32_t x) { asm volatile("st.volatile.shared.u32 [%0], %1;" :: "r"(a), "r"(x) : "memory"); }
__device__ __forceinline__ uint4 ldsm4(uint32_t a) { uint4 v; asm volatile("ldmatrix.sync.aligned.m8n8.x4.shared.b16 {%0,%1,%2,%3}, [%4];" : "=r"(v.x), "=r"(v.y), "=r"(v.z), "=r"(v.w) : "r"(a) : "memory"); return v; }
__device__ __forceinline__ uint4 ldsm4t(uint32_t a) { uint4 v; asm volatile("ldmatrix.sync.aligned.m8n8.x4.trans.shared.b16 {%0,%1,%2,%3}, [%4];" : "=r"(v.x), "=r"(v.y), "=r"(v.z), "=r"(v.w) : "r"(a) : "memory"); return v; }
__device__ __forceinline__ uint4 ldsm4t_if(uint32_t a, uint32_t c) { uint4 v; asm volatile("{.reg .pred p; setp.ne.u32 p, %5, 0; @p ldmatrix.sync.aligned.m8n8.x4.trans.shared.b16 {%0,%1,%2,%3}, [%4];}" : "=r"(v.x), "=r"(v.y), "=r"(v.z), "=r"(v.w) : "r"(a), "r"(c) : "memory"); return v; }
__device__ __forceinline__ uint4 lds128_if(uint32_t a, uint32_t c) { uint4 v; asm volatile("{.reg .pred p; setp.ne.u32 p, %5, 0; @p ld.volatile.shared.v4.u32 {%0,%1,%2,%3}, [%4];}" : "=r"(v.x), "=r"(v.y), "=r"(v.z), "=r"(v.w) : "r"(a), "r"(c) : "memory"); return v; }
__device__ __forceinline__ void stsm4(uint32_t a, uint32_t x, uint32_t y, uint32_t z, uint32_t w) { asm volatile("stmatrix.sync.aligned.m8n8.x4.shared.b16 [%0], {%1,%2,%3,%4};" :: "r"(a), "r"(x), "r"(y), "r"(z), "r"(w) : "memory"); }
__device__ __forceinline__ void stsm4t(uint32_t a, uint32_t x, uint32_t y, uint32_t z, uint32_t w) { asm volatile("stmatrix.sync.aligned.m8n8.x4.trans.shared.b16 [%0], {%1,%2,%3,%4};" :: "r"(a), "r"(x), "r"(y), "r"(z), "r"(w) : "memory"); }
__device__ __forceinline__ void bar_sync(int id, int n) { asm volatile("bar.sync %0, %1;" :: "r"(id), "r"(n) : "memory"); }
__device__ __forceinline__ void bar_sync_if(int id, int n, bool c) { asm volatile("{.reg .pred p; setp.ne.u32 p, %2, 0; @p bar.sync %0, %1;}" :: "r"(id), "r"(n), "r"((uint32_t)c) : "memory"); }
__device__ __forceinline__ void mbar_init(uint32_t a, uint32_t c) { asm volatile("mbarrier.init.shared::cta.b64 [%0], %1;" :: "r"(a), "r"(c) : "memory"); }
__device__ __forceinline__ void mbar_arrive(uint32_t a) { asm volatile("mbarrier.arrive.shared::cta.b64 _, [%0];" :: "r"(a) : "memory"); }
__device__ __forceinline__ void mbar_arrive_tx(uint32_t a, uint32_t tx) { asm volatile("mbarrier.arrive.expect_tx.shared::cta.b64 _, [%0], %1;" :: "r"(a), "r"(tx) : "memory"); }
__device__ __forceinline__ void spin_guard(uint32_t n) { asm volatile("{.reg .pred p; setp.gt.u32 p, %0, %1; @p st.shared.u32 [%0], %0;}" :: "r"(n), "n"(SPIN_LIMIT) : "memory"); }
__device__ __forceinline__ void mbar_wait(uint32_t a, uint32_t ph) {
    asm volatile("{\n.reg .pred p, q;\n.reg .u32 n;\nmov.u32 n, 0;\n"
                 "MW_LOOP:\nmbarrier.try_wait.parity.shared::cta.b64 p, [%0], %1;\n"
                 "add.u32 n, n, 1;\nsetp.gt.u32 q, n, %2;\n@q st.shared.u32 [n], n;\n@!p bra.uni MW_LOOP;\n}"
                 :: "r"(a), "r"(ph), "n"(SPIN_LIMIT) : "memory");
}
__device__ __forceinline__ uint32_t mbar_try(uint32_t a, uint32_t ph) {
    uint32_t ok;
    asm volatile("{.reg .pred p; mbarrier.test_wait.parity.shared::cta.b64 p, [%1], %2; selp.u32 %0, 1, 0, p;}" : "=r"(ok) : "r"(a), "r"(ph) : "memory");
    return ok;
}
__device__ __forceinline__ void wait_clk(uint32_t c0, uint32_t d) {
    asm volatile("{\n.reg .pred p;\n.reg .u32 c;\n.reg .u64 x;\nWC_LOOP:\nmov.u64 x, %%clock64;\ncvt.u32.u64 c, x;\nsub.u32 c, c, %0;\nsetp.lt.s32 p, c, %1;\n@p bra.uni WC_LOOP;\n}" :: "r"(c0), "r"(d) : "memory");
}
__device__ __forceinline__ void sts32_if(uint32_t a, uint32_t x, bool c) { asm volatile("{.reg .pred p; setp.ne.u32 p, %2, 0; @p st.volatile.shared.u32 [%0], %1;}" :: "r"(a), "r"(x), "r"((uint32_t)c) : "memory"); }
__device__ __forceinline__ float rcp(float x) { float y; asm("rcp.approx.ftz.f32 %0, %1;" : "=f"(y) : "f"(x)); return y; }
__device__ __forceinline__ float uf(uint32_t x) { return __uint_as_float(x); }
__device__ __forceinline__ void mbar_arrive_remote_if(uint32_t a, bool c) { asm volatile("{.reg .pred p; setp.ne.u32 p, %1, 0; @p mbarrier.arrive.relaxed.cluster.shared::cluster.b64 _, [%0];}" :: "r"(a), "r"((uint32_t)c) : "memory"); }
__device__ __forceinline__ void mbar_arrive_if(uint32_t a, bool c) { asm volatile("{.reg .pred p; setp.ne.u32 p, %1, 0; @p mbarrier.arrive.shared::cta.b64 _, [%0];}" :: "r"(a), "r"((uint32_t)c) : "memory"); }
__device__ __forceinline__ void mbar_arrive_tx_if(uint32_t a, uint32_t tx, bool c) { asm volatile("{.reg .pred p; setp.ne.u32 p, %2, 0; @p mbarrier.arrive.expect_tx.shared::cta.b64 _, [%0], %1;}" :: "r"(a), "r"(tx), "r"((uint32_t)c) : "memory"); }
__device__ __forceinline__ void tma2d(uint32_t dst, const CUtensorMap* m, int c0, int c1, uint32_t mb) {
    asm volatile("cp.async.bulk.tensor.2d.shared::cluster.global.mbarrier::complete_tx::bytes [%0], [%1, {%2, %3}], [%4];" :: "r"(dst), "l"(m), "r"(c0), "r"(c1), "r"(mb) : "memory");
}
__device__ __forceinline__ void tma3d(uint32_t dst, const CUtensorMap* m, int c0, int c1, int c2, uint32_t mb) {
    asm volatile("cp.async.bulk.tensor.3d.shared::cluster.global.mbarrier::complete_tx::bytes [%0], [%1, {%2, %3, %4}], [%5];" :: "r"(dst), "l"(m), "r"(c0), "r"(c1), "r"(c2), "r"(mb) : "memory");
}
__device__ __forceinline__ void tma_xn(uint32_t dst, const CUtensorMap* m, int g, uint32_t mb) {
    asm volatile("{.reg .pred p; elect.sync _|p, 0xffffffff;\n@p mbarrier.arrive.expect_tx.shared::cta.b64 _, [%2], 40960;\n"
                 "@p cp.async.bulk.tensor.3d.shared::cluster.global.mbarrier::complete_tx::bytes [%0], [%1, {0, %3, 0}], [%2];}" :: "r"(dst), "l"(m), "r"(mb), "r"(32 * g) : "memory");
}
__device__ __forceinline__ void tma2d_prefetch(const CUtensorMap* m, int c0, int c1) {
    asm volatile("cp.async.bulk.prefetch.tensor.2d.L2.global [%0, {%1, %2}];" :: "l"(m), "r"(c0), "r"(c1) : "memory");
}
__device__ __forceinline__ void st_async128_if(uint32_t a, float x, float y, float z, float w, uint32_t mb, bool c) {
    asm volatile("{.reg .pred p; setp.ne.u32 p, %6, 0; @p st.async.shared::cluster.mbarrier::complete_tx::bytes.v4.f32 [%0], {%1,%2,%3,%4}, [%5];}" :: "r"(a), "f"(x), "f"(y), "f"(z), "f"(w), "r"(mb), "r"((uint32_t)c) : "memory");
}
__device__ __forceinline__ void st_async128(uint32_t a, float x, float y, float z, float w, uint32_t mb) {
    asm volatile("st.async.shared::cluster.mbarrier::complete_tx::bytes.v4.f32 [%0], {%1,%2,%3,%4}, [%5];" :: "r"(a), "f"(x), "f"(y), "f"(z), "f"(w), "r"(mb) : "memory");
}
__device__ __forceinline__ void st_async32(uint32_t a, uint32_t x, uint32_t mb) {
    asm volatile("st.async.shared::cluster.mbarrier::complete_tx::bytes.b32 [%0], %1, [%2];" :: "r"(a), "r"(x), "r"(mb) : "memory");
}
__device__ __forceinline__ void st_async64(uint32_t a, uint32_t x, uint32_t y, uint32_t mb) {
    asm volatile("st.async.shared::cluster.mbarrier::complete_tx::bytes.v2.b32 [%0], {%1,%2}, [%3];" :: "r"(a), "r"(x), "r"(y), "r"(mb) : "memory");
}
__device__ __forceinline__ void st_async64_if(uint32_t a, uint32_t x, uint32_t y, uint32_t mb, bool c) {
    asm volatile("{.reg .pred p; setp.ne.u32 p, %4, 0; @p st.async.shared::cluster.mbarrier::complete_tx::bytes.v2.b32 [%0], {%1,%2}, [%3];}" :: "r"(a), "r"(x), "r"(y), "r"(mb), "r"((uint32_t)c) : "memory");
}
__device__ __forceinline__ void bulk_g2s(uint32_t dst, const void* src, uint32_t bytes, uint32_t mb) {
    asm volatile("cp.async.bulk.shared::cluster.global.mbarrier::complete_tx::bytes [%0], [%1], %2, [%3];" :: "r"(dst), "l"(src), "r"(bytes), "r"(mb) : "memory");
}
__device__ __forceinline__ void bulk_g2s_mc(uint32_t dst, const void* src, uint32_t bytes, uint32_t mb, uint16_t mask) {
    asm volatile("cp.async.bulk.shared::cluster.global.mbarrier::complete_tx::bytes.multicast::cluster [%0], [%1], %2, [%3], %4;" :: "r"(dst), "l"(src), "r"(bytes), "r"(mb), "h"(mask) : "memory");
}
__device__ __forceinline__ void bulk_s2s(uint32_t dst, uint32_t src, uint32_t bytes, uint32_t mb) {
    asm volatile("cp.async.bulk.shared::cluster.shared::cta.mbarrier::complete_tx::bytes [%0], [%1], %2, [%3];" :: "r"(dst), "r"(src), "r"(bytes), "r"(mb) : "memory");
}
__device__ __forceinline__ void bulk_s2g(void* dst, uint32_t src, uint32_t bytes) {
    asm volatile("cp.async.bulk.global.shared::cta.bulk_group [%0], [%1], %2;\ncp.async.bulk.commit_group;" :: "l"(dst), "r"(src), "r"(bytes) : "memory");
}
__device__ __forceinline__ void bulk_prefetch(const void* p, uint32_t bytes) { asm volatile("cp.async.bulk.prefetch.L2.global [%0], %1;" :: "l"(p), "r"(bytes) : "memory"); }
__device__ __forceinline__ void bulk_wait_all() { asm volatile("cp.async.bulk.wait_group 0;" ::: "memory"); }
__device__ __forceinline__ void fence_release() { asm volatile("fence.release.gpu;" ::: "memory"); }
__device__ __forceinline__ void fence_async() { asm volatile("fence.proxy.async.global;" ::: "memory"); }
__device__ __forceinline__ void fence_async_smem() { asm volatile("fence.proxy.async.shared::cta;" ::: "memory"); }
__device__ __forceinline__ void bar_arrive(int id, int n) { asm volatile("bar.arrive %0, %1;" :: "r"(id), "r"(n) : "memory"); }
__device__ __forceinline__ uint32_t ld_acquire(const uint32_t* p) { uint32_t v; asm volatile("ld.acquire.gpu.global.u32 %0, [%1];" : "=r"(v) : "l"(p) : "memory"); return v; }
__device__ __forceinline__ void wait_flag(const uint32_t* p, uint32_t target) { uint32_t n = 0; while ((int)(ld_acquire(p) - target) < 0) { spin_guard(++n); __nanosleep(64); } }
__device__ __forceinline__ void wg_fence() { asm volatile("wgmma.fence.sync.aligned;" ::: "memory"); }
__device__ __forceinline__ void wg_commit() { asm volatile("wgmma.commit_group.sync.aligned;" ::: "memory"); }
template <int N> __device__ __forceinline__ void wg_wait() { asm volatile("wgmma.wait_group.sync.aligned %0;" :: "n"(N) : "memory"); }
__device__ __forceinline__ uint32_t wg_desc_lo(uint32_t addr, uint32_t lbo) { return ((addr & 0x3FFFF) >> 4) | ((lbo >> 4) << 16); }
constexpr uint32_t WG_DESC_HI = (1024u >> 4) | (1u << 30);
template <int ACC>
__device__ __forceinline__ void wgmma_n32_rs(float (&c)[16], const uint4& a, uint64_t d) {
    asm volatile("wgmma.mma_async.sync.aligned.m64n32k16.f32.f16.f16 {%0,%1,%2,%3,%4,%5,%6,%7,%8,%9,%10,%11,%12,%13,%14,%15},{%16,%17,%18,%19},%20,%21,1,1,0;"
        : "+f"(c[0]), "+f"(c[1]), "+f"(c[2]), "+f"(c[3]), "+f"(c[4]), "+f"(c[5]), "+f"(c[6]), "+f"(c[7]),
          "+f"(c[8]), "+f"(c[9]), "+f"(c[10]), "+f"(c[11]), "+f"(c[12]), "+f"(c[13]), "+f"(c[14]), "+f"(c[15])
        : "r"(a.x), "r"(a.y), "r"(a.z), "r"(a.w), "l"(d), "n"(ACC));
}
__device__ __forceinline__ uint4 ld_relaxed128(const void* p) { uint4 v; asm volatile("ld.relaxed.gpu.global.v4.u32 {%0,%1,%2,%3}, [%4];" : "=r"(v.x), "=r"(v.y), "=r"(v.z), "=r"(v.w) : "l"(p) : "memory"); return v; }
__device__ __forceinline__ uint2 ld_relaxed64(const void* p) { uint2 v; asm volatile("ld.relaxed.gpu.global.v2.u32 {%0,%1}, [%2];" : "=r"(v.x), "=r"(v.y) : "l"(p) : "memory"); return v; }
__device__ __forceinline__ void ld_relaxed128_if(uint4& v, const void* p, uint32_t c) { asm volatile("{.reg .pred p; setp.ne.u32 p, %5, 0; @p ld.relaxed.gpu.global.v4.u32 {%0,%1,%2,%3}, [%4];}" : "+r"(v.x), "+r"(v.y), "+r"(v.z), "+r"(v.w) : "l"(p), "r"(c) : "memory"); }
__device__ __forceinline__ void ld_relaxed64_if(uint4& v, const void* p, uint32_t c) { asm volatile("{.reg .pred p; setp.ne.u32 p, %3, 0; @p ld.relaxed.gpu.global.v2.u32 {%0,%1}, [%2];}" : "+r"(v.x), "+r"(v.y) : "l"(p), "r"(c) : "memory"); }
__device__ __forceinline__ void st_relaxed128(void* p, uint4 v) { asm volatile("st.relaxed.gpu.global.v4.u32 [%0], {%1,%2,%3,%4};" :: "l"(p), "r"(v.x), "r"(v.y), "r"(v.z), "r"(v.w) : "memory"); }
__device__ __forceinline__ uint32_t ld_relaxed32(const void* p) { uint32_t v; asm volatile("ld.relaxed.gpu.global.u32 %0, [%1];" : "=r"(v) : "l"(p) : "memory"); return v; }
__device__ __forceinline__ void st_relaxed32(void* p, uint32_t v) { asm volatile("st.relaxed.gpu.global.u32 [%0], %1;" :: "l"(p), "r"(v) : "memory"); }
__device__ __forceinline__ void red_h8(void* p, uint32_t a, uint32_t b, uint32_t c, uint32_t d) {
    asm volatile("red.relaxed.gpu.global.add.noftz.v4.f16x2 [%0], {%1,%2,%3,%4};" :: "l"(p), "r"(a), "r"(b), "r"(c), "r"(d) : "memory");
}
__device__ __forceinline__ void red_h4(void* p, uint32_t a, uint32_t b) {
    asm volatile("red.relaxed.gpu.global.add.noftz.v2.f16x2 [%0], {%1,%2};" :: "l"(p), "r"(a), "r"(b) : "memory");
}
__device__ __forceinline__ void red_add_if(uint32_t* p, uint32_t v, bool c) { asm volatile("{.reg .pred p; setp.ne.u32 p, %2, 0; @p red.relaxed.gpu.global.add.u32 [%0], %1;}" :: "l"(p), "r"(v), "r"((uint32_t)c) : "memory"); }
__device__ __forceinline__ uint32_t ldg32(const void* p) { uint32_t v; asm volatile("ld.global.nc.L1::no_allocate.u32 %0, [%1];" : "=r"(v) : "l"(p)); return v; }
__device__ __forceinline__ unsigned char* rec_ptr(int h, int s) { return g_rec + (uint32_t)((h * NSEG + s) * REC_BYTES); }
__device__ __forceinline__ float bf16_round(float x) { return __uint_as_float(pack_bf16(0.0f, x)); }

#define A_RES 7
#define B_RES 8
#define A_DISP 6
#define B_DISP 5
#define A_P1 2
#define A_P2 6
#define A_P3 7
#define B_P1 4
#define B_P2 8
#define A_RL 0
#define B_RL 2
#define A_DEPTH 3
#define B_DEPTH 4
#define VXN_AT 7
#define PH_AT 0
#define CARRY 2
#define VX_PRE 4
#define AM_AT 0
#define SPEC_ST 1
#define V_SPLIT 10
#define POLL_EARLY 850
#define A_SPLIT 17
#define B_SPLIT 12
#define LATE_AT 6
#define NO_MAX 20
#define V_ST_FIRST 0
#define SIG_DEAD 100
#define SIG_V 30
#define SIG_POLL 400
#define A_RL2 3
#define P1_ILP 2
#define PQ_AT 8
#define SWAP_AB 0
#define EARLY_P 8
#define POLL_MEM 0
#define PRE_ILP 2
#define XN_AT 1
#define XN_NAP 0
#define A_ILP 2
#define B_ACC2 0
#define POLL_MAX 4000
#define PUB_LATE 1
#define V_TAIL 0
#define V_LEAD 0
#define V_DEPTH 4
#define TP_SPLIT 12
#define OB_DEP 0
#define B_GO -1
#define A_P0 0
#define V_PACE 1
#define P_PACE 0
#define KX_AT 5
#define G_WAIT 0
#define V_SEND 1
#define G_NAP 40
#define E_NAP 300
#define B_ADV 0
#define V_SEP 0
#define B_HOLD 0
#define PF_MODE 0
#define PF_NAP 0
#define W_DEPTH_V 3
#define G_PACE 200
#define PF_FROM 40
#define V_ORDER 1
#define XN_EARLY 0
#define V_POLL 0
#define WG_DELAY 0
#define VW_DELAY 0
#define RL_PRE 0
#define MB_DEPTH 3
constexpr int X_RES = 5, A_SW = 24 - X_RES, B_SW = 16 - X_RES, T_SW = A_SW + B_SW, T_DISP = A_DISP + B_DISP;
constexpr int SM_BASE = 1024;
constexpr uint32_t SM_RANK = 1u << 24;
constexpr int SM_FO = 0;
constexpr int SM_XP = 61440;
constexpr int SM_KT0 = SM_XP + 4096;
constexpr int SM_MEM = SM_KT0 + 4096, MV = 608;
constexpr int SM_KT1 = 81920;
constexpr int SM_XQ = SM_KT1 + 4096;
constexpr int SM_QM = SM_XQ + 4096, SM_KMM = SM_QM + 1024;
constexpr int SM_ONE = SM_KMM + 256, SM_USC = SM_KMM + 768;
constexpr int SM_SLOC = SM_KMM + 2048;
constexpr int SM_OB = SM_SLOC + 1536;
constexpr int SM_LS = SM_OB + 2048;
constexpr int SM_SREM = SM_LS + 1024;
constexpr int SM_VM = SM_SREM + 1536;
constexpr int SM_FQ = SM_VM + 2048;
constexpr int SM_VX = 167936, SM_VX2 = SM_VX + 8192;
constexpr int SM_XN = 184320;
static_assert(T_SW <= 30 && SM_MEM + 20 * MV <= SM_KT1 && SM_FQ + T_DISP * 2048 <= SM_VX, "smem layout");
constexpr int SM_CST = 229376;
constexpr int SM_BAR = SM_CST + 64;
constexpr int MB_S = SM_BAR, MB_V = SM_BAR + 8, MB_VX = SM_BAR + 16, MB_VF = SM_BAR + 16  , MB_PUB = SM_BAR + 32  ,
              MB_XN = SM_BAR + 56, MB_XNF = SM_BAR + 64, MB_KT = SM_BAR + 72, MB_KTF = SM_BAR + 80,
              MB_PF = SM_BAR + 104  , MB_PE = SM_BAR + 168  , MB_GO = SM_BAR + 192, MB_PO = SM_BAR + 256  ,
              MB_ST = SM_BAR  , MB_R = SM_BAR + 96, MB_RDY = SM_BAR + 48, MB_OM = SM_BAR + 88, MB_MEM = SM_BAR + 200, MB_XN2 = SM_BAR + 208, MB_CST = SM_BAR + 216;
static_assert(MB_V == MB_S + 8 && MB_VX == MB_S + 16, "barriers");
constexpr int SM_XN2 = 0;
constexpr int SM_AT = 81920, MB_AT = SM_BAR + 224  ;
constexpr int NVR = 6, SM_VR = SM_AT + 2 * REC_BYTES;
constexpr int NKM = 8, SM_KM = 40960, MB_KM = SM_BAR + 320  ;
constexpr int SM_MEMV = SM_VR + NVR * 8192;
constexpr int SM_AO0 = SM_KM + NKM * 4096, SM_AO1 = SM_XN - 8192;
static_assert(SM_AO0 + 8192 <= SM_AT && SM_MEMV + 20 * MV <= SM_AO1, "smem layout");
static_assert(SM_MEMV >= 163840 && SM_MEMV + 20 * MV <= SM_XN && SM_KM + NKM * 4096 <= SM_AT, "smem layout");
constexpr int SM_PROF = SM_BAR + 320;
constexpr int MB_L0 = SM_PROF + 112  , MB_LN = SM_PROF + 128  , LN_WARPS = LN_CTAS * 8;
constexpr int CHAIN_SMEM = SM_PROF + 512;
static_assert(CHAIN_SMEM <= 232448, "smem");
constexpr int STG_O = 0, STG_QK = 81920, STG_V = 0;

constexpr int BAR_MEMA = 1, BAR_MEMB = 2, BAR_PAIR = 3  , BAR_RED = 7, BAR_O = 8, BAR_ALL = 9, BAR_C = 10, BAR_BGO = 11, BAR_PW = 12, BAR_LATE = 13, BAR_MEM = 14  ;
#define QK_PRE 3
#define B_W1 11
#define B_W2 B_SW
#define A_PRE2 8
#define POLL_DELAY_A 150
constexpr uint32_t CNT_ONE = 0x3c003c00u, CNT_FULL = 0x50005000u, BF_ONES = 0x3f803f80u;

struct Maps { CUtensorMap q, k, v, o, xnp, xn, q64, o64, wg, wu, wd; };
struct Ptrs { const __nv_bfloat16 *x, *mem0, *wr, *wq, *wk, *wv, *wo; __nv_bfloat16* out; uint32_t zero; uint64_t desc, desc_b, desc_oa; uint32_t sb0, sbv; };

__device__ __forceinline__ uint32_t launch_tag() { return *(volatile uint32_t*)&g_epoch * NSEG + 1; }
__device__ __forceinline__ uint32_t* launch_flags() { return g_flags[*(volatile uint32_t*)&g_epoch & 1]; }
__device__ __forceinline__ void flag_add(uint32_t* p) { asm volatile("red.release.gpu.global.add.u32 [%0], 1;" :: "l"(p) : "memory"); }
__device__ __forceinline__ void wait_count(uint32_t a, uint32_t v) {
    uint32_t n = 0, x;
    while (true) {
        asm volatile("ld.acquire.cta.shared.u32 %0, [%1];" : "=r"(x) : "r"(a) : "memory");
        if (__all_sync(~0u, x >= v)) break;
        spin_guard(++n >> 2);
    }
}
constexpr int SM_PH = SM_CST + 60;
constexpr int SM_RC = SM_BAR + 240;
constexpr int SM_AD = SM_BAR + 304;
__device__ __forceinline__ void wait_att(uint32_t sb, int g) {
    uint32_t n = 0;
    while (lds32(sb + SM_AD + (g & 1) * 4) <= (uint32_t)(g >> 1)) spin_guard(++n >> 4);
}
__device__ __forceinline__ uint32_t opaque(uint32_t x) { asm volatile("" : "+r"(x)); return x; }
__device__ __forceinline__ uint32_t pin(uint32_t x) { return __shfl_sync(~0u, x, threadIdx.x & 31); }
__device__ __forceinline__ void sfence(uint32_t z) { asm volatile("{.reg .pred p; setp.ne.u32 p, %0, 0; @p griddepcontrol.launch_dependents;}" :: "r"(z) : "memory"); }
__device__ __forceinline__ float lg2(float x) { float y; asm("lg2.approx.ftz.f32 %0, %1;" : "=f"(y) : "f"(x)); return y; }
__device__ __forceinline__ uint2 ldsm2t(uint32_t a) { uint2 v; asm volatile("ldmatrix.sync.aligned.m8n8.x2.trans.shared.b16 {%0,%1}, [%2];" : "=r"(v.x), "=r"(v.y) : "r"(a) : "memory"); return v; }
__device__ __forceinline__ uint32_t exp_or_mark(float z) {
    uint32_t e;
    asm volatile("{.reg .pred p; .reg .f32 a; .reg .b32 m; ex2.approx.ftz.f32 %0, %1; abs.f32 a, %1; setp.gtu.f32 p, a, 0f42200000; shf.r.wrap.b32 m, %1, 1, 1; selp.b32 %0, m, %0, p;}" : "=&r"(e) : "r"(__float_as_uint(z)));
    return e;
}
__device__ __forceinline__ uint32_t after(uint32_t a, uint32_t x, uint32_t z) { return a | (x & z); }

__device__ __forceinline__ uint32_t absmax2(uint32_t a, uint32_t b) { uint32_t d; asm("max.xorsign.abs.bf16x2 %0, %1, %2;" : "=r"(d) : "r"(a), "r"(b)); return d; }
__device__ __forceinline__ uint32_t absmax8(uint32_t a, const uint4& x) { return absmax2(absmax2(a, absmax2(x.x, x.y)), absmax2(x.z, x.w)); }
__device__ __forceinline__ uint32_t warp_absmax(uint32_t a) { return __reduce_max_sync(~0u, max((a & 0x7fffu) << 16, a & 0x7fff0000u)); }
__device__ __forceinline__ uint32_t tile_off(int ch0, int lane, int al) {
    const int sg = lane & 7, row = 4 * al + (sg >> 1) + 8 * (sg & 1);
    return row * 128 + (((ch0 + ((lane >> 3) & 1)) ^ (row & 7)) << 4);
}
template <class F>
__device__ __forceinline__ uint32_t load_tile(uint4 (&w)[20], int& ke, uint32_t slot0, uint32_t dslot, int ch0, int lane, uint32_t zr, F released) {
    const uint32_t o0 = slot0 + tile_off(ch0, lane, 0), o1 = slot0 + tile_off(ch0, lane, 1), mh = lane >> 4, dj = dslot - 20480;
    uint32_t a = 0;
#pragma unroll
    for (int k = 0; k < 20; k++) {
        const uint32_t o = ((k >> 1) & 1) ? o1 : o0;
        const int n = k < 16 ? 8 * (k & 1) + (k >> 2) : 16 + 2 * (k & 1);
        w[k] = ldsm4t(o + n * 2048 + (k >= 16 ? dj + mh * 2048 : n >= 10 ? dj + mh * 8192 : n >= 8 ? mh * (dj + 8192) : mh * 8192));
    }
#pragma unroll
    for (int k = 0; k < 20; k++) a = absmax8(a, w[k]);
    a = warp_absmax(a);
    released(a);
    ke = f16_exp(uf(a));
    uint32_t s2 = (uint32_t)(127 + ke) * 0x00800080u;
#pragma unroll
    for (int k = 0; k < 20; k++) {
        w[k].x = bf16x2_to_f16x2p(w[k].x, s2); w[k].y = bf16x2_to_f16x2p(w[k].y, s2); w[k].z = bf16x2_to_f16x2p(w[k].z, s2); w[k].w = bf16x2_to_f16x2p(w[k].w, s2);
        if (k & 1) s2 = after(s2, w[k].x, zr);
    }
    return a;
}
__device__ __forceinline__ uint32_t all_of(const uint4 (&w)[20]) {
    uint32_t a = 0;
#pragma unroll
    for (int k = 0; k < 20; k++) a |= w[k].w;
    return a;
}

template <bool FIRST = true, bool LAST = true, int K0 = 0, int K1 = 20>
__device__ __forceinline__ void tp_issue(float (&c)[16], const uint4 (&w)[20], uint32_t xn, uint64_t dbase) {
    const uint64_t d0 = dbase + ((SM_BASE + xn) >> 4);
    if (FIRST || K0) wg_fence();
#pragma unroll
    for (int k = K0; k < K1; k++) {
        const uint64_t d = d0 + (((k >> 2) * 4096 + (k & 3) * 32) >> 4);
        if (k == 0 && FIRST) wgmma_n32_rs<0>(c, w[k], d); else wgmma_n32_rs<1>(c, w[k], d);
    }
    if (LAST) wg_commit();
}
__device__ __forceinline__ void tp_dump_k(uint32_t bt, float (&c)[16], float ik) {
#pragma unroll
    for (int n = 0; n < 2; n++) sts128(bt + SM_XP + n * 2048, pack_bf16(c[8 * n] * ik, c[8 * n + 1] * ik), pack_bf16(c[8 * n + 2] * ik, c[8 * n + 3] * ik), pack_bf16(c[8 * n + 4] * ik, c[8 * n + 5] * ik), pack_bf16(c[8 * n + 6] * ik, c[8 * n + 7] * ik));
}
__device__ __forceinline__ uint32_t kt_lane(uint32_t sb, int t, int lane) { return sb + (t >> 1) * 2048 + (t & 1) * 256 + (lane >> 4) * 512 + (lane & 15) * 16; }
__device__ __forceinline__ void tp_combine_k(uint32_t sb, uint32_t bt, uint32_t dst, const float (&c)[16], float ik, bool first) {
    const uint4 x = lds128(bt + SM_XP), y = lds128(bt + SM_XP + 2048);
    uint32_t w[8] = {x.x, x.y, x.z, x.w, y.x, y.y, y.z, y.w};
#pragma unroll
    for (int n = 0; n < 8; n++) w[n] = pack_bf16(fmaf(c[2 * n], ik, uf(w[n] << 16)), fmaf(c[2 * n + 1], ik, uf(w[n] & 0xffff0000u)));
    stsm4(dst, w[0], w[1], w[2], w[3]);
    stsm4(dst + 1024, w[4], w[5], w[6], w[7]);
    __syncwarp();
    mbar_arrive_if(sb + MB_KT, first);
}
template <class F>
__device__ __forceinline__ void tpv_issue(float (&c)[16], const uint4 (&w0)[20], const uint4 (&w1)[20], int seg, uint64_t dbase, F mid) {
    dbase -= (seg & 1) * ((SM_XN - SM_XN2) >> 4);
    tp_issue<true, true, 0, V_SPLIT>(c, w0, SM_XN, dbase);
    mid();
    tp_issue<false, false, V_SPLIT, 20>(c, w0, SM_XN, dbase);
    tp_issue<false, true>(c, w1, SM_XN + 5 * 4096, dbase);
}
__device__ __forceinline__ void tpv_store(uint32_t dst, const float (&c)[16], float iv) {
    sts128(dst, pack_bf16(c[0] * iv, c[1] * iv), pack_bf16(c[2] * iv, c[3] * iv), pack_bf16(c[4] * iv, c[5] * iv), pack_bf16(c[6] * iv, c[7] * iv));
    sts128(dst + 2048, pack_bf16(c[8] * iv, c[9] * iv), pack_bf16(c[10] * iv, c[11] * iv), pack_bf16(c[12] * iv, c[13] * iv), pack_bf16(c[14] * iv, c[15] * iv));
}
__device__ __forceinline__ uint32_t hmul2(uint32_t a, uint32_t b) { uint32_t d; asm("mul.rn.f16x2 %0, %1, %2;" : "=r"(d) : "r"(a), "r"(b)); return d; }
__device__ __forceinline__ uint32_t hmax2abs(uint32_t a, uint32_t b) { uint32_t d; asm("max.xorsign.abs.f16x2 %0, %1, %2;" : "=r"(d) : "r"(a), "r"(b)); return d; }
__device__ __forceinline__ int out_scale(uint32_t sb, float usc, int lane) {
    uint32_t a = 0;
#pragma unroll 4
    for (int u = 0; u < NO_MAX; u++) { const uint4 m = lds128(sb + SM_MEM + (lane + (lane >> 3) * 2) * 16 + u * MV); a = hmax2abs(hmax2abs(a, hmax2abs(m.x, m.y)), hmax2abs(m.z, m.w)); }
    const uint2 c = lds64(sb + SM_CST + 32);
    a = __reduce_max_sync(~0u, hmax2abs(a, a >> 16) & 0x7fffu);
    return f16_exp(__uint_as_float(c.x) * fmaxf(__uint_as_float(c.y), 25.4f * usc * __half2float(__ushort_as_half((unsigned short)a))));
}

__device__ __forceinline__ int mem0_exp(const __nv_bfloat16* __restrict__ mem0, int lane) {
    uint32_t a = 0;
    uint4 y[20];
#pragma unroll
    for (int n = 0; n < 20; n++) y[n] = __ldg(reinterpret_cast<const uint4*>(mem0) + n * 32 + lane);
#pragma unroll
    for (int n = 0; n < 20; n++) a = absmax8(a, y[n]);
    return f16_exp(__uint_as_float(warp_absmax(a)));
}
__device__ __forceinline__ float mem0_frags(uint32_t sb, uint32_t mem, const __nv_bfloat16* __restrict__ mem0, int kh, int t, int lane) {
    const unsigned short* m0 = reinterpret_cast<const unsigned short*>(mem0) + (lane >> 2) * DM + 320 * kh + (lane & 3);
    uint32_t r[3][4];
#pragma unroll
    for (int n = 0; n < 3; n++) {
        const int u = min(t + 4 * n, 9);
#pragma unroll
        for (int i = 0; i < 4; i++) {
            const int d = n < 2 ? 16 * (u >> 1) + 64 * i + 4 * (u & 1) : 16 * i + 256 + 4 * (u - 8);
            r[n][i] = (uint32_t)__ldg(m0 + d) | ((uint32_t)__ldg(m0 + d + 8) << 16);
        }
    }
    const int ke = lds32(sb + SM_CST + (kh * 4 + t) * 4);
    const uint32_t s2 = (uint32_t)(127 + ke) * 0x00800080u, a = mem + (kh * 10 + t) * MV + (lane + (lane >> 3) * 2) * 16;
#pragma unroll
    for (int n = 0; n < 3; n++)
        if (n < 2 || t < 2) sts128(a + n * 4 * MV, bf16x2_to_f16x2p(r[n][0], s2), bf16x2_to_f16x2p(r[n][1], s2), bf16x2_to_f16x2p(r[n][2], s2), bf16x2_to_f16x2p(r[n][3], s2));
    return pow2i(-ke);
}
struct MemAddr {
    uint32_t wa0, wa2, r1;
    __device__ __forceinline__ void init(uint32_t mem, int kh, int t, int ln) {
        const uint32_t wa = mem + (kh * 10 + (ln >> 4)) * MV + (10 * (ln & 3) + ((ln >> 2) & 3)) * 16;
        wa0 = pin(wa + t * 2 * MV);
        wa2 = pin(kh ? t * 4096 + 2048 + 128 + ring_pos(ln >> 4) + (ln & 15) * 8 : wa + 8 * MV + t * 4);
        r1 = pin(t * 4096 + ring_pos(ln >> 3) + (ln & 7) * 16 + kh * 128);
    }
};
__device__ __forceinline__ unsigned char* ring_ptr(uint32_t r, int s, int j) {
    uint64_t p;
    asm("mov.b64 %0, {%1, %2};" : "=l"(p) : "r"(r | opaque((uint32_t)(uintptr_t)g_ring + (s & 1) * 512 + ((s & 2) + j) * 16384)), "r"((uint32_t)((uintptr_t)g_ring >> 32)));
    return reinterpret_cast<unsigned char*>(p);
}
struct MemWords {
    uint4 a, b, c, d;
    template <bool E>
    __device__ __forceinline__ void load(const unsigned char* p, const unsigned char* q) {
        a = ld_relaxed128(p); c = ld_relaxed128(p + 16384);
        if (E) { const uint2 x = ld_relaxed64(q), y = ld_relaxed64(q + 16384); b = make_uint4(x.x, x.y, 0, 0); d = make_uint4(y.x, y.y, 0, 0); }
        else { b = ld_relaxed128(p + 2048); d = ld_relaxed128(p + 16384 + 2048); }
    }
    template <bool E>
    __device__ __forceinline__ uint32_t missing() const { uint32_t x; asm("lop3.b32 %0, %1, %2, %3, 0x2a;" : "=r"(x) : "r"(a.w & c.w & (E ? b.y : b.w)), "r"(E ? d.y : d.w), "n"(CNT_FULL)); return x; }
    template <bool E>
    __device__ __forceinline__ void store(const MemAddr& ma, uint32_t z) const {
        if (E) { sts128(ma.wa0 + 64, a.z, b.x, c.z, d.x); sts128(ma.wa0, a.x, a.y, after(c.x, a.z, z), after(c.y, a.w, z)); }
        else {
            sts128(ma.wa0, a.x, a.y, a.z, after(c.x, a.w, z)); sts128(ma.wa0 + 64, b.x, b.y, b.z, after(d.x, b.w, z));
            sts32(ma.wa2 + 10 * MV, c.z); sts32(ma.wa2 + 10 * MV + 64, d.z); sts32(ma.wa2, c.y); sts32(ma.wa2 + 64, d.y);
        }
    }
};
template <bool E>
__device__ __forceinline__ void fetch_issue(MemWords& m, int s, const MemAddr& ma, uint32_t tp, uint32_t d, uint32_t zr) {
    const unsigned char* p = ring_ptr(ma.r1, s - 1, 0), * q = ring_ptr(ma.wa2, s - 1, 0);
    sfence(zr);
    wait_clk(tp, d);
    m.load<E>(p, q);
}
template <bool E>
__device__ __forceinline__ void fetch_store(MemWords& m, int s, const MemAddr& ma, uint32_t zr, int fail) {
    if (s == 0) return;
    uint32_t n = 1;
    const uint32_t bad = m.missing<E>();
    if (SPEC_ST) m.store<E>(ma, zr);
    if (__any_sync(~0u, bad)) {
        const unsigned char* p = ring_ptr(ma.r1, s - 1, 0), * q = ring_ptr(ma.wa2, s - 1, 0);
#pragma unroll 1
        do {
            spin_guard(++n);
            m.load<E>(p, q);
        } while (__any_sync(~0u, m.missing<E>()));
        if (SPEC_ST) m.store<E>(ma, zr);
    }
    if (!SPEC_ST) m.store<E>(ma, zr);
}

__device__ __forceinline__ uint32_t* stamp_ptr(int h) { return g_stamp + (h >> 2) * 256 + (h & 3) * 4; }
__device__ __forceinline__ uint32_t post_time(int h, int r, int s, int ns, bool first) {
    const uint32_t c = clk(), g0 = gtime_lo();
    uint32_t g, n = 0;
    do g = gtime_lo(); while (g == g0 && ++n < 64);
    const uint32_t own = (g + ns - ((clk() - c) * 145 >> 8)) << 6 | s;
    if (first) st_relaxed32(stamp_ptr(h) + r, own);
    return own;
}
__device__ __forceinline__ int lead_time(int h, uint32_t own, int lane) {
    int late;
#pragma unroll 1
    for (int n = 0; n < 16; n++) {
        const uint4 x = ld_relaxed128(stamp_ptr(lane));
        const uint32_t d0 = x.x - own, d1 = x.y - own, d2 = x.z - own;
        late = max(max((d0 & 63) ? 0 : (int)d0, (d1 & 63) ? 0 : (int)d1), (d2 & 63) ? 0 : (int)d2);
        if (__all_sync(~0u, ((d0 | d1 | d2) & 63) == 0)) break;
    }
    return max(min((__reduce_max_sync(~0u, late) - __shfl_sync(~0u, late, h)) >> 6, 1200) * 452 / 256 - SIG_DEAD, 0);
}

#define zr P.zero
__device__ __forceinline__ void vs_main(uint32_t sb, int h_, int w_, int lane_, const Ptrs& P, const Maps* maps) {
    float usc;
    lane_ = __shfl_sync(~0u, lane_, lane_);
    const uint32_t cfg_ = __shfl_sync(~0u, w_ | h_ << 3, 0);
    float iv;
    uint4 w0[20], w1[20];
    float c[16];
    constexpr uint32_t rd0 = -2 * SM_RANK, rd1 = -SM_RANK;
    const uint32_t vr = sb + SM_VR + (w_ & 1) * 4096 + (w_ >> 1) * 512 + lane_ * 16;
    auto send_v = [&](int g, uint32_t slot) {
        const uint32_t src = sb + SM_VR + slot, dst = sb + ((g & 1) ? SM_VX2 : SM_VX);
        fence_async_smem();
        bulk_s2s(dst + rd0, src, 8192, sb + rd0 + MB_VX); bulk_s2s(dst + rd1, src, 8192, sb + rd1 + MB_VX);
    };

    {
        const int lane = lane_, t = cfg_ & 3, kh = (cfg_ >> 2) & 1;
        usc = mem0_frags(sb, sb + SM_MEMV, P.mem0, kh, t, lane);
        const uint32_t slot = sb + STG_V + 4 * kh * 20480;
        uint32_t a = 0;
        int k0 = 0, k1 = 0;
#pragma unroll 1
        for (int n = 0; n < 2; n++) {
#pragma unroll
            for (int k = 0; k < 20; k++) w0[k] = w1[k];
            k0 = k1;
            mbar_wait(sb + MB_PF + (4 * kh + 2 * n) * 8, 0); mbar_wait(sb + MB_PF + (4 * kh + 2 * n + 1) * 8, 0);
            a = max(a, load_tile(w1, k1, slot + n * 40960, 20480, 2 * t, lane, zr, [](uint32_t) {}));
        }
        if (lane == 0) { atomicMax(launch_flags() + F_WV, a); mbar_arrive(sb + MB_OM); }
        if (k0 != k1) {
            const int km = min(k0, k1);
            const uint32_t f0 = (uint32_t)max(15 + km - k0, 0) * 0x04000400u, f1 = (uint32_t)max(15 + km - k1, 0) * 0x04000400u;
#pragma unroll
            for (int k = 0; k < 20; k++) {
                w0[k].x = hmul2(w0[k].x, f0); w0[k].y = hmul2(w0[k].y, f0); w0[k].z = hmul2(w0[k].z, f0); w0[k].w = hmul2(w0[k].w, f0);
                w1[k].x = hmul2(w1[k].x, f1); w1[k].y = hmul2(w1[k].y, f1); w1[k].z = hmul2(w1[k].z, f1); w1[k].w = hmul2(w1[k].w, f1);
            }
            k0 = km;
        }
        iv = pow2i(-k0);
        bar_sync(BAR_ALL, 256);
        if (w_ == 0 && lane == 0) GTM(5);
        mbar_arrive_if(sb + MB_GO, lane == 0);
        mbar_arrive_remote_if(sb + rd0 + MB_RDY, w_ == 0 && lane_ == 0); mbar_arrive_remote_if(sb + rd1 + MB_RDY, w_ == 0 && lane_ == 0);
#pragma unroll 1
        for (int g = 0;; g++) {
            mbar_wait(sb + (g ? MB_XN2 : MB_XN), 0);
            if (g) bar_sync(BAR_ALL, 256);
            tpv_issue(c, w0, w1, g, P.desc, [] {});
            if (g) break;
            wg_wait<0>();
            mbar_arrive_if(sb + MB_XNF, lane == 0);
            tpv_store(vr, c, iv);
        }
        mbar_wait(sb + MB_RDY, 0);
        if (w_ == 0 && lane == 0) send_v(0, 0);
        __syncwarp();
        if (w_ == 0 && lane == 0) GTM(7);
    }
    const int w = __reduce_max_sync(~0u, w_), h = __reduce_max_sync(~0u, h_);
    MemAddr ma;
    ma.init(sb + SM_MEMV, w >> 2, w & 3, lane_);
    const uint32_t memr = pin(sb + SM_MEMV + (lane_ + (lane_ >> 3) * 2) * 16), b8w = pin(sb + lane_ * 8 + (w & 1) * 1024 + (w >> 1) * 256);
    uint32_t vslot = 0, c0 = clk() - POLL_DELAY;
    sfence(zr & (memr ^ b8w ^ ma.r1 ^ ma.wa0 ^ ma.wa2));
#pragma unroll 1
    for (int s = 0;; s++) {
        const uint32_t ph = s & 1;
        const bool lane0 = (b8w & 255) == 0, first = lane0 && w == 0;
        if (s + 1 >= NVR) wait_att(sb, s + 1 - NVR);
        mbar_arrive_tx_if(sb + MB_R, 12, first && s < NSEG - 1);
        if (s + 2 < NSEG && w == 2) mbar_wait(sb + MB_XN + ph * (MB_XN2 - MB_XN), ((s >> 1) + 1) & 1);
        vslot = vslot == (NVR - 1) * 8192 ? 0 : vslot + 8192;
        if (V_ST_FIRST) { wg_wait<0>(); tpv_store(2 * b8w + (vslot + SM_VR - sb + (w & 1) * 2048), c, iv); }
        MemWords mw;
        if (w >= 4) fetch_issue<true>(mw, s, ma, c0, 0, zr); else fetch_issue<false>(mw, s, ma, c0, POLL_DELAY - POLL_EARLY, zr);
        sfence(zr);
        if (!V_ST_FIRST) { wg_wait<0>(); tpv_store(2 * b8w + (vslot + SM_VR - sb + (w & 1) * 2048), c, iv); sfence(zr); }
        if (w >= 4) { fetch_store<true>(mw, s, ma, zr, s < 4 ? -1 : 3); bar_sync(BAR_MEM + 1, 128); }
        else { fetch_store<false>(mw, s, ma, zr, s < 4 ? -1 : 2); bar_sync(BAR_MEM, 256); }
        uint4 mb[20];
        float p0[4] = {0, 0, 0, 0}, p1[4] = {0, 0, 0, 0}, p2[4] = {0, 0, 0, 0}, p3[4] = {0, 0, 0, 0};
        auto vec = [](int u) { return u < 8 ? 10 + u : u < 18 ? u - 8 : u; };
#pragma unroll
        for (int u = 0; u < V_DEPTH; u++) mb[u] = lds128(memr + vec(u) * MV);
        asm volatile("{.reg .pred p; setp.ne.u32 p, %2, 0; @p st.relaxed.gpu.global.u32 [%0], %1;}" :: "l"(stamp_ptr(h) + 2), "r"((gtime_lo() + SIG_V) * 64 + s + 1), "r"((uint32_t)first) : "memory");
        sfence(zr);
#pragma unroll
        for (int u = 0; u < 20; u++) {
            const int v = vec(u);
            const uint4 &a = v < 10 ? w0[2 * v % 20] : w1[2 * v % 20], &b = v < 10 ? w0[2 * v % 20 + 1] : w1[2 * v % 20 + 1];
            if (u & 1) { mma16816h(p2, a, mb[u].x, mb[u].y); mma16816h(p3, b, mb[u].z, mb[u].w); }
            else { mma16816h(p0, a, mb[u].x, mb[u].y); mma16816h(p1, b, mb[u].z, mb[u].w); }
            if (u + V_DEPTH < 20) sfence(zr);
            if (u + V_DEPTH == 8) bar_sync_if(BAR_MEM, 256, w >= 4);
            if (u + V_DEPTH < 20) mb[u + V_DEPTH] = lds128(memr + vec(u + V_DEPTH) * MV);
            if (u == PH_AT) sts32_if(sb + SM_PH, 2 * s + 1, first);
        }
        const float f = iv * usc;
        const uint32_t y0 = pack_bf16(fmaf(p2[0] + p3[0], f, (p0[0] + p1[0]) * f), fmaf(p2[1] + p3[1], f, (p0[1] + p1[1]) * f));
        const uint32_t y1 = pack_bf16(fmaf(p2[2] + p3[2], f, (p0[2] + p1[2]) * f), fmaf(p2[3] + p3[3], f, (p0[3] + p1[3]) * f));
        st_async64(b8w + rd0 + SM_VM, y0, y1, sb + rd0 + MB_V);
        st_async64(b8w + rd1 + SM_VM, y0, y1, sb + rd1 + MB_V);
        sts64(b8w + SM_KM + (s % NKM) * 4096 + 2048, y0, y1);
KMDUMP(        *reinterpret_cast<uint2*>(g_kmd + (uint32_t)((h * NSEG + s) * 4096 + 2048 + w * 256 + lane_ * 8)) = make_uint2(y0, y1);)
        if (w == 7 && s + 3 < NSEG) {
            if (s == 1) mbar_wait(sb + MB_CST, 0);
            if (s < 2) fence_async();
            tma_xn(sb + SM_XN2 + ph * (SM_XN - SM_XN2), &maps->xnp, s + 3, sb + MB_XN2 - ph * (MB_XN2 - MB_XN));
        }
        bar_sync(BAR_ALL, 256);
        mbar_arrive_tx_if(sb + MB_KM + (s & 7) * 8, 2048, first);
        if (w == 0) VT(s, 0);
        if (__builtin_expect(s == NSEG - 1, 0)) break;
        tpv_issue(c, w0, w1, s, P.desc, [&] {
            if (w == 1) {
                if (lane0) { sts32(sb + SM_PH, 2 * s + 2); if (s + 2 < NSEG) send_v(s + 1, vslot); }
                __syncwarp();
            }
        });
        mbar_wait(sb + MB_R, ph);
        c0 = clk();
        { const uint4 cp = lds128(sb + SM_RC); c0 += min(max((int)(cp.x + cp.z - c0), -POLL_DELAY), POLL_MAX); usc = uf(cp.y); }
    }
}

template <bool ISA>
__device__ __forceinline__ void load_wo(uint32_t sb, uint4 (&wx)[X_RES], int t, int lane, const Ptrs& P) {
    constexpr int NOT = ISA ? 3 : 2, NSW = ISA ? A_SW : B_SW;
    const int m = lane >> 3, sg = lane & 7;
    uint4 wo[NOT * 8];
#pragma unroll
    for (int i = 0; i < NOT; i++) {
        const int co = 16 * t + 64 * (i + (ISA ? 0 : 3)) + 8 * (m & 1);
        const uint32_t base = sb + STG_O + (co >> 6) * 16384 + (8 * (m >> 1) + sg) * 128 + ((((co & 63) >> 3) ^ sg) << 4);
#pragma unroll
        for (int T = 0; T < 8; T++) wo[T * NOT + i] = ldsm4t(base + T * 2048);
    }
    uint32_t all = 0;
#pragma unroll
    for (int f = 0; f < NOT * 8; f++) all = absmax8(all, wo[f]);
    all = warp_absmax(all);
    if (lane == 0) { atomicMax(launch_flags() + F_WO, all); mbar_arrive(sb + MB_OM); }
    bar_sync(after(BAR_ALL, all, zr), 256);
#pragma unroll
    for (int f = 0; f < X_RES; f++) wx[f] = wo[NSW + f];
#pragma unroll
    for (int f = 0; f < NSW; f++) sts128(sb + lane * 16 + SM_FO + t * 512 + ((ISA ? 0 : A_SW) + f) * 2048, wo[f]);
}
template <bool ISA>
__device__ __forceinline__ void chain_loop(uint32_t sb, int h, int j, int t, int lane, const Ptrs& P, uint4 (&wq)[20], const uint4 (&wk)[20], const uint4 (&wx)[X_RES],
                                           float (&c)[16], float usc, float iq, float ik);
__device__ __forceinline__ void chain_main(uint32_t sb, int h, int j, int w_, int lane_, const Ptrs& P) {
    lane_ = __shfl_sync(~0u, lane_, lane_);
    const int w = __reduce_max_sync(~0u, w_), kh = w >> 2, t = w & 3, lane = lane_;
    float iq, ik;
    float c[16];
    uint4 wq[20], wk[20], wx[X_RES];
#pragma unroll 1
    for (int i = 0; i < 5; i++) mbar_wait(sb + MB_PO + i * 8, 0);
    if (w == 0 && lane == 0) GTM(3);
    if (kh == 0) load_wo<true>(sb, wx, t, lane, P); else load_wo<false>(sb, wx, t, lane, P);
    const float usc = mem0_frags(sb, sb + SM_MEM, P.mem0, kh, t, lane);
#pragma unroll 1
    for (int n = 0; n < 2; n++) {
        const int c0 = 4 * n + 2 * kh;
        const uint32_t s0 = sb + STG_QK + (c0 % 5) * 20480, ds = ((c0 + 1) % 5 - c0 % 5) * 20480;
        mbar_wait(sb + MB_PF + c0 * 8, 0); mbar_wait(sb + MB_PF + c0 * 8 + 8, 0);
        int kw;
        load_tile(wq, kw, s0, ds, 2 * t, lane, zr, [&](uint32_t d) { mbar_arrive_if(after(sb + MB_PE + kh * 8, d, zr), lane == 0 && n == 0); });
        iq = pow2i(-kw);
        if (n) break;
        ik = iq;
#pragma unroll
        for (int k = 0; k < 20; k++) wk[k] = wq[k];
        if (w == 0 && lane == 0) GTM(4);
#pragma unroll 1
        for (int g = 0;; g++) {
            mbar_wait(sb + MB_XN, g);
            tp_issue<true, true, 0, B_SPLIT>(c, wk, SM_XN + kh * 5 * 4096, P.desc);
            if (g) break;
            tp_issue<false, true, B_SPLIT, 20>(c, wk, SM_XN + kh * 5 * 4096, P.desc);
            wg_wait<0>();
            mbar_arrive_if(sb + MB_XNF, lane == 0);
            if (kh == 0) tp_dump_k(sb + t * 512 + lane * 16, c, ik);
            bar_sync(BAR_PAIR + t, 64);
            if (kh) tp_combine_k(sb, sb + t * 512 + lane * 16, kt_lane(sb, t, lane) + SM_KT0, c, ik, lane == 0);
        }
        wg_wait<0>();
    }
    bar_sync(BAR_ALL, 256);
    if (w == 0 && lane == 0) GTM(5);
    iq *= 0.08838834764831845f * 1.4426950408889634f;
    if (kh == 0) chain_loop<true>(sb, h, j, t, lane, P, wq, wk, wx, c, usc, iq, ik);
    else chain_loop<false>(sb, h, j, t, lane, P, wq, wk, wx, c, usc, iq, ik);
}
template <bool ISA>
__device__ __forceinline__ void chain_loop(uint32_t sb, int h, int j, int t, int lane, const Ptrs& P, uint4 (&wq)[20], const uint4 (&wk)[20], const uint4 (&wx)[X_RES],
                                           float (&c)[16], float usc, float iq, float ik) {
    constexpr int KH = ISA ? 0 : 1;
    constexpr int NOT = ISA ? 3 : 2;
    constexpr int NRES = ISA ? A_RES : B_RES, NSW = NOT * 8 - NRES, NDISP = ISA ? A_DISP : B_DISP, DEPTH = ISA ? A_DEPTH : B_DEPTH;
    constexpr int FO = SM_FO + (ISA ? 0 : A_SW) * 2048, FQ = SM_FQ + (ISA ? 0 : A_DISP) * 2048;
    const uint32_t b0l = pin(sb + lane * 16), bt = pin(sb + lane * 16 + t * 512), b8l = pin(sb + lane * 8), b8t = pin(sb + lane * 8 + t * 256);
    const uint32_t memr = pin(sb + SM_MEM + KH * 10 * MV + (lane + (lane >> 3) * 2) * 16);
    const uint32_t mat = !ISA ? 0 : pin(sb + SM_QM + (lane & 7) * 16 + (lane < 16 ? (t >> 1) * 512 + (t & 1) * 128 + (lane & 8) * 32 : 1024 + t * 512 + (lane & 8) * 16));
#pragma unroll
    for (int k = 0; k < NDISP; k++) sts128(bt + FQ + k * 2048, wq[k]);
    if (ISA) sts128(sb + SM_ONE, BF_ONES, BF_ONES, BF_ONES, BF_ONES);
    bar_sync(BAR_ALL, 256);
    if (ISA && t == 0 && lane == 0) GTM(7);
    const uint32_t rdelta = (1 - 2 * j) * SM_RANK, rdelta2 = (2 - j) * SM_RANK;
    if (ISA) { mbar_arrive_remote_if(sb + rdelta + MB_RDY, t == 0 && lane == 0); mbar_arrive_remote_if(sb + rdelta2 + MB_RDY, t == 0 && lane == 0); }
    mbar_wait(sb + MB_RDY, 0);
    const uint32_t srem = ISA ? pin(b8t + rdelta + SM_SREM) : 0, mrem = ISA ? pin(sb + rdelta + MB_S) : 0;
    if (ISA) mbar_wait(sb + MB_KTF, 0);
    uint4 wr_[NRES];
#pragma unroll
    for (int f = 0; f < NRES; f++) wr_[f] = f < NRES - X_RES ? lds128(bt + FO + (NSW + f) * 2048) : wx[f < NRES - X_RES ? 0 : f - (NRES - X_RES)];
    MemAddr ma;
    ma.init(sb + SM_MEM, KH, t, lane);
    constexpr int RL = ISA ? A_RL : B_RL, SPLIT = ISA ? A_SPLIT : B_SPLIT;
    if (SPLIT > B_SPLIT) tp_issue<false, true, B_SPLIT, SPLIT>(c, wk, SM_XN + KH * 5 * 4096, P.desc);
    uint32_t c0 = clk() - POLL_DELAY;
    sfence(zr & (wr_[0].x ^ wr_[1].x ^ wr_[2].x ^ wr_[3].x ^ ma.wa0 ^ memr ^ b0l ^ b8l ^ b8t ^ mat ^ srem ^ mrem ^ ma.r1 ^ ma.wa2));

#pragma unroll 1
    for (int s = 0;; s++) {
        const uint32_t ph = s & 1;
        const bool first = (b8l & 255) == 0;
        MemWords mw;
        fetch_issue<!ISA>(mw, s, ma, c0, ISA ? POLL_DELAY : POLL_EARLY, zr);
        sfence(zr);
        tp_issue<false, true, SPLIT, 20>(c, wk, SM_XN + KH * 5 * 4096, P.desc);
#pragma unroll
        for (int kk = RL; kk < (ISA ? A_RL2 : NDISP); kk++) wq[kk] = lds128(bt + FQ + kk * 2048);
        wg_wait<0>();
        mbar_arrive_if(sb + MB_XNF, first);
        if (ISA) {
            bar_sync(BAR_PAIR + t, 64);
            tp_combine_k(sb, bt, b0l + (b0l & 256) + ((t >> 1) * 2048 + (t & 1) * 256 + SM_KT1 - ph * (SM_KT1 - SM_KT0)), c, ik, first && s < NSEG - 1);
            sfence(zr);
#pragma unroll
            for (int kk = A_RL2; kk < NDISP; kk++) wq[kk] = lds128(bt + FQ + kk * 2048);
        } else { tp_dump_k(bt, c, ik); bar_arrive(BAR_PAIR + t, 64); }
        sfence(zr);
        fetch_store<!ISA>(mw, s, ma, zr, s < 4 ? -1 : KH);
        if (ISA) bar_arrive(BAR_LATE, 256);
        bar_sync(BAR_MEM + KH, ISA && B_GO >= 0 ? 256 : 128);
        float q[4] = {0, 0, 0, 0}, k[4] = {0, 0, 0, 0}, q2[4] = {0, 0, 0, 0}, k2[4] = {0, 0, 0, 0};
        uint4 mb[10], wo[NOT * 8], kx0, kx1, pq, pk;
#pragma unroll
        for (int u = 0; u < DEPTH; u++) mb[u] = lds128(memr + u * MV);
        sfence(zr);
#pragma unroll
        for (int u = 0; u < 10; u++) {
            mma16816h(q2, wq[2 * u], mb[u].x, mb[u].y);
            mma16816h(k2, wk[2 * u], mb[u].x, mb[u].y);
            mma16816h(q, wq[2 * u + 1], mb[u].z, mb[u].w);
            mma16816h(k, wk[2 * u + 1], mb[u].z, mb[u].w);
            if (u == 0) TS(KH, 0, mb[0].x);
            sfence(zr);
            if (u + DEPTH < (ISA ? 10 : 8)) mb[u + DEPTH] = lds128(memr + (u + DEPTH) * MV);
            if (u == 0) mbar_arrive_if(sb + MB_MEM, first && s > 0);
            if (!ISA && u == B_GO) bar_arrive(BAR_MEM, 256);
            if (!ISA && u == LATE_AT) { bar_sync(BAR_LATE, 256); mb[8] = lds128(memr + 8 * MV); mb[9] = lds128(memr + 9 * MV); sfence(zr); }
            if (ISA && u == KX_AT) kx0 = ldsm4t(bt + (SM_KT0 + ph * (SM_KT1 - SM_KT0)));
            if (ISA && u == KX_AT + 1) kx1 = ldsm4t(bt + (SM_KT0 + ph * (SM_KT1 - SM_KT0)) + 2048);
            if (ISA && u == PQ_AT) { bar_sync(BAR_PAIR + t, 64); pq = lds128(bt + SM_XQ); pk = lds128(bt + SM_XQ + 2048); sfence(zr); }
        }
        float l0, l1;
        const float fq = usc * iq, fk = usc * ik;
        auto scores = [&](uint32_t a, const uint4& y0, const uint4& y1, auto mid) {
            const uint4 x0 = ldsm4t(b0l + SM_QM), x1 = ldsm4t(b0l + SM_QM + 512);
            mid();
            float z[4][4];
#pragma unroll
            for (int n = 0; n < 4; n++) z[n][0] = z[n][1] = z[n][2] = z[n][3] = 0;
            mma16816(z[0], x0, y0.x, y0.y); mma16816(z[1], x0, y0.z, y0.w); mma16816(z[2], x1, y1.x, y1.y); mma16816(z[3], x1, y1.z, y1.w);
            const float z0 = (z[0][0] + z[1][2]) + (z[2][0] + z[3][2]), z1 = (z[0][1] + z[1][3]) + (z[2][1] + z[3][3]);
            const uint32_t e0 = exp_or_mark(z0), e1 = exp_or_mark(z1);
            if (ISA) st_async64(srem, e0, e1, mrem); else st_async64((a ^ SM_RANK) + SM_SREM, e0, e1, (sb ^ SM_RANK) + MB_S);
            sts64(a + SM_SLOC, e0, e1);
            return make_uint2(e0, e1);
        };
        auto publish = [&]() {
            const uint2 km = ldsm2t(bt + SM_KMM);
            st_async64(b8t + rdelta2 + SM_KM + (s % NKM) * 4096 + j * 1024, km.x, km.y, SM_BASE + 2 * SM_RANK + MB_KM + (s & 7) * 8);
KMDUMP(            *reinterpret_cast<uint2*>(g_kmd + (uint32_t)((h * NSEG + s) * 4096 + (4 * j + t) * 256 + lane * 8)) = km;)
            mbar_arrive_if(sb + MB_PUB + ph * 8, first);
        };
        if (ISA) {
            stsm4(mat,
                  pack_bf16(fmaf(q[0], fq, fmaf(q2[0], fq, uf(pq.x))), fmaf(q[1], fq, fmaf(q2[1], fq, uf(pq.y)))), pack_bf16(fmaf(q[2], fq, fmaf(q2[2], fq, uf(pq.z))), fmaf(q[3], fq, fmaf(q2[3], fq, uf(pq.w)))),
                  pack_bf16(fmaf(k[0], fk, fmaf(k2[0], fk, uf(pk.x))), fmaf(k[1], fk, fmaf(k2[1], fk, uf(pk.y)))), pack_bf16(fmaf(k[2], fk, fmaf(k2[2], fk, uf(pk.z))), fmaf(k[3], fk, fmaf(k2[3], fk, uf(pk.w)))));
            bar_sync(BAR_RED, 192);
            uint4 vx[4];
            const uint2 own = scores(b8t, kx0, kx1, [&] {
                sfence(zr);
#pragma unroll
                for (int i = 0; i < VX_PRE; i++) vx[i] = lds128(bt + (SM_VX + ph * 8192) + i * 2048);
                sfence(zr);
            });
            TS(0, 1, 0);
            bar_sync(BAR_BGO, 256);
            if (s == NSEG - 1) { mbar_wait(sb + MB_S, 1); mbar_wait(sb + MB_V, 1); break; }
            uint2 lo[5];
#pragma unroll
            for (int i = 0; i < 5; i++) lo[i] = lds64(b8l + SM_SLOC + i * 256);
            const uint4 one = lds128(sb + SM_ONE);
#pragma unroll
            for (int i = VX_PRE; i < 4; i++) vx[i] = lds128(bt + (SM_VX + ph * 8192) + i * 2048);
#pragma unroll
            for (int f = 0; f < A_P1; f++) wo[f] = lds128(bt + FO + f * 2048);
            sfence(zr);
            uint32_t neg = ((lo[0].x | lo[0].y | lo[1].x) | (lo[1].y | lo[2].x | lo[2].y) | (lo[3].x | lo[3].y) | (lo[4].x | lo[4].y));
            mbar_wait(sb + MB_S, ph);
            TS(0, 2, 0);
            uint2 r[5];
#pragma unroll
            for (int i = 0; i < 5; i++) r[i] = lds64(b8l + SM_SREM + i * 256);
            const uint32_t vok = mbar_try(sb + MB_V, ph);
            neg = (neg | own.x | own.y) & 0x80000000u;
            uint32_t p[5];
#pragma unroll
            for (int i = 0; i < 5; i++) p[i] = pack_bf16(uf(lo[i].x) * uf(r[i].x), uf(lo[i].y) * uf(r[i].y));
            neg = (opaque(opaque(neg | p[0] | p[1]) | p[2] | p[3]) | p[4]) & 0x80008000u;
            if (__builtin_expect(__any_sync(~0u, neg || !vok), 0)) {
                mbar_wait(sb + MB_V, ph);
                if (__any_sync(~0u, neg)) {
                    float sv[10], mx = -INFINITY;
#pragma unroll
                    for (int i = 0; i < 10; i++) {
                        const uint32_t a = lds32(b8l + SM_SLOC + (i >> 1) * 256 + (i & 1) * 4), b = lds32(b8l + SM_SREM + (i >> 1) * 256 + (i & 1) * 4);
                        sv[i] = ((int)a < 0 ? uf(a << 1) : lg2(uf(a))) + ((int)b < 0 ? uf(b << 1) : lg2(uf(b)));
                        mx = fmaxf(mx, sv[i]);
                    }
                    mx = fmaxf(mx, __shfl_xor_sync(~0u, mx, 1));
                    mx = fmaxf(mx, __shfl_xor_sync(~0u, mx, 2));
#pragma unroll
                    for (int i = 0; i < 5; i++) p[i] = pack_bf16(ex2(sv[2 * i] - mx), ex2(sv[2 * i + 1] - mx));
                }
            }
            const uint2 vm0 = lds64(b8t + SM_VM), vm1 = lds64(b8t + SM_VM + 1024);
            float o0[4] = {0, 0, 0, 0}, o1[4] = {0, 0, 0, 0}, ls[4] = {0, 0, 0, 0};
            mma16816(o0, vx[0], p[0], p[1]); mma16816(o1, vx[2], p[0], p[1]);
            mma16816(ls, one, p[0], p[1]);
            sfence(zr);
#pragma unroll
            for (int f = A_P1; f < A_P2; f++) wo[f] = lds128(bt + FO + f * 2048);
            sfence(zr);
            mma16816(o0, vx[1], p[2], p[3]); mma16816(o1, vx[3], p[2], p[3]);
            mma16816(ls, one, p[2], p[3]);
            mma1688(o0, vm0.x, vm0.y, p[4]); mma1688(o1, vm1.x, vm1.y, p[4]);
            mma1688(ls, one.x, one.y, p[4]);
            stsm4(bt + SM_OB, pack_bf16(o0[0], o0[1]), pack_bf16(o0[2], o0[3]), pack_bf16(o1[0], o1[1]), pack_bf16(o1[2], o1[3]));
            l0 = ls[0]; l1 = ls[1];
            sts64(b8t + SM_LS, __float_as_uint(l0), __float_as_uint(l1));
        } else {
            sts128f(bt + SM_XQ, fmaf(q[0], fq, q2[0] * fq), fmaf(q[1], fq, q2[1] * fq), fmaf(q[2], fq, q2[2] * fq), fmaf(q[3], fq, q2[3] * fq));
            sts128f(bt + SM_XQ + 2048, fmaf(k[0], fk, k2[0] * fk), fmaf(k[1], fk, k2[1] * fk), fmaf(k[2], fk, k2[2] * fk), fmaf(k[3], fk, k2[3] * fk));
            bar_arrive(BAR_PAIR + t, 64);
            sfence(zr);
            {
                uint32_t fa = bt;
#pragma unroll
                for (int f = 0; f < B_P1; f++) { wo[f] = lds128(fa + FO + f * 2048); if (f % P1_ILP == P1_ILP - 1) fa = after(bt, wo[f].x, zr); }
            }
            if (t == 0) { bar_sync(BAR_RED, 192); const uint4 y0 = ldsm4t(b0l + (b0l & 256) + SM_KMM), y1 = ldsm4t(b0l + (b0l & 256) + SM_KMM + 1024); scores(b8l + 1024, y0, y1, [] {}); }
            bar_sync(BAR_BGO, 256);
            publish();
            if (s == NSEG - 1) break;
            {
                uint32_t fa = bt;
#pragma unroll
                for (int f = B_P1; f < B_P2; f++) { wo[f] = lds128(fa + FO + f * 2048); if ((f - B_P1) % PRE_ILP == PRE_ILP - 1) fa = after(bt, wo[f].x, zr); }
            }
        }
        unsigned char* wr1 = ring_ptr(ma.r1, s, j), * wr2 = ring_ptr(ma.wa2, s, j);
        if (!ISA) {
            uint32_t x = 0;
#pragma unroll
            for (int f = 0; f < B_P2; f++) x |= wo[f].x;
            sfence(zr & x);
        }
        bar_sync(BAR_O, 288);
        float acc[NOT][4], acd[NOT][4];
#pragma unroll
        for (int i = 0; i < NOT; i++) { acc[i][0] = acc[i][1] = acc[i][2] = acc[i][3] = 0; acd[i][0] = acd[i][1] = acd[i][2] = acd[i][3] = 0; }
        {
            uint4 ob[4];
            ob[0] = ldsm4t(b0l + SM_OB);
            if (!ISA) { ob[1] = ldsm4t(b0l + SM_OB + 512); ob[2] = ldsm4t(b0l + SM_OB + 1024); }
            c0 = clk();
            if (ISA) ob[1] = ldsm4t(b0l + SM_OB + 512);
            else { const uint2 l = lds64(b8t + SM_LS); l0 = uf(l.x); l1 = uf(l.y); }
            usc = uf(lds32(b8l + SM_USC));
            sfence(zr);
#pragma unroll
            for (int T = 0; T < 8; T++) {
                const uint32_t b0 = (T & 1) ? ob[T >> 1].z : ob[T >> 1].x, b1 = (T & 1) ? ob[T >> 1].w : ob[T >> 1].y;
#pragma unroll
                for (int i = 0; i < NOT; i++) {
                    const int f = T * NOT + i;
                    const uint4& a = f >= NSW ? wr_[f >= NSW ? f - NSW : 0] : wo[f];
                    if (!(T & 1) && !ISA) mma16816(acd[i], a, b0, b1); else mma16816(acc[i], a, b0, b1);
                }
                if (ISA) {
                    if (T < 6) sfence(zr);
                    if (T == 1 || T == 3) { ob[T / 2 + 2] = ldsm4t(b0l + SM_OB + (T / 2 + 2) * 512); sfence(zr); }
#pragma unroll
                    for (int f = T ? A_P3 + 3 * T : A_P2; f < A_P3 + 3 * (T + 1) && f < NSW; f++) wo[f] = lds128(bt + FO + f * 2048);
                    if (T == 4) { l0 = rcp(l0 * usc); l1 = rcp(l1 * usc); }
                    if (T < 4) sfence(zr);
                } else if (T == 1) {
                    sfence(zr);
                    ob[3] = ldsm4t(b0l + SM_OB + 1536);
#pragma unroll
                    for (int f = B_P2; f < NSW; f++) wo[f] = lds128(bt + FO + f * 2048);
                    sfence(zr);
                } else if (T == 3) {
                    sfence(zr);
                    l0 = rcp(l0 * usc); l1 = rcp(l1 * usc);
                }
            }
#pragma unroll
            for (int i = 0; i < NOT; i++) {
                if (ISA) { acc[i][0] *= l0; acc[i][1] *= l1; acc[i][2] *= l0; acc[i][3] *= l1; }
                else { acc[i][0] = fmaf(acc[i][0], l0, acd[i][0] * l0); acc[i][1] = fmaf(acc[i][1], l1, acd[i][1] * l1); acc[i][2] = fmaf(acc[i][2], l0, acd[i][2] * l0); acc[i][3] = fmaf(acc[i][3], l1, acd[i][3] * l1); }
            }
        }
        if (ISA) {
            red_h8(wr1, pack_f16(acc[0][0], acc[0][2]), pack_f16(acc[1][0], acc[1][2]), pack_f16(acc[NOT - 1][0], acc[NOT - 1][2]), CNT_ONE);
            red_h8(wr1 + 2048, pack_f16(acc[0][1], acc[0][3]), pack_f16(acc[1][1], acc[1][3]), pack_f16(acc[NOT - 1][1], acc[NOT - 1][3]), CNT_ONE);
        } else {
            red_h8(wr1, pack_f16(acc[0][0], acc[0][2]), pack_f16(acc[1][0], acc[1][2]), pack_f16(acc[0][1], acc[0][3]), CNT_ONE);
            red_h4(wr2, pack_f16(acc[1][1], acc[1][3]), CNT_ONE);
        }
        TS(KH, 3, __float_as_uint(acc[0][0]));
        bar_sync(BAR_PW, 288);
        const uint32_t lead = lds32(b8l + SM_USC + 4);
#pragma unroll
        for (int kk = 0; kk < RL; kk++) wq[kk] = lds128(bt + FQ + kk * 2048);
        tp_issue<true, true, 0, SPLIT>(c, wk, SM_XN + KH * 5 * 4096, P.desc);
        sfence(zr);
        c0 += __reduce_max_sync(~0u, lead);
    }
#undef zr
}

template <class F>
__device__ __forceinline__ void att_pass(uint32_t rec, uint32_t out, uint32_t vt, uint32_t kmr, int up, int lane, F half) {
    float sc[5][4];
#pragma unroll
    for (int i = 0; i < 5; i++) sc[i][0] = sc[i][1] = sc[i][2] = sc[i][3] = 0;
    const uint32_t rl = rec + lane * 16, kl = rec + REC_K + (lane >> 4) * 512 + (lane & 15) * 16;
#pragma unroll S_UNROLL
    for (int T = 0; T < 8; T++) {
        const uint4 q = lds128(rl + REC_Q + up * 4096 + T * 512), k1 = ldsm4t(kl + (T >> 1) * 2048 + (T & 1) * 256 + up * 1024);
        const uint2 km = lds64(kmr + T * 256);
        mma16816(sc[3], q, k1.x, k1.y); mma16816(sc[4], q, k1.z, k1.w);
        mma16816(sc[0], q, km.x, km.y);
        if (up) { const uint4 k0 = ldsm4t(kl + (T >> 1) * 2048 + (T & 1) * 256); mma16816(sc[1], q, k0.x, k0.y); mma16816(sc[2], q, k0.z, k0.w); }
    }
    const int dg = (lane >> 2) - 2 * (lane & 3);
    if (dg < 0) sc[3][0] = sc[4][2] = -INFINITY;
    if (dg < 1) sc[3][1] = sc[4][3] = -INFINITY;
    sc[4][0] = sc[4][1] = -INFINITY;
    if (!up) {
#pragma unroll
        for (int i = 0; i < 4; i++) sc[1][i] = sc[2][i] = -INFINITY;
    }
    float m0 = fmaxf(sc[0][0], sc[0][1]), m1 = fmaxf(sc[0][2], sc[0][3]);
#pragma unroll
    for (int i = 1; i < 5; i++) { m0 = fmaxf(m0, fmaxf(sc[i][0], sc[i][1])); m1 = fmaxf(m1, fmaxf(sc[i][2], sc[i][3])); }
#pragma unroll
    for (int o = 1; o < 4; o <<= 1) { m0 = fmaxf(m0, __shfl_xor_sync(~0u, m0, o)); m1 = fmaxf(m1, __shfl_xor_sync(~0u, m1, o)); }
    uint32_t pl[5], ph[5];
    const float fq = 0.08838834764831845f * 1.4426950408889634f;
    m0 *= -fq; m1 *= -fq;
    float l0 = 0, l1 = 0;
#pragma unroll
    for (int i = 0; i < 5; i++) {
        sc[i][0] = ex2(fmaf(sc[i][0], fq, m0)); sc[i][1] = ex2(fmaf(sc[i][1], fq, m0)); sc[i][2] = ex2(fmaf(sc[i][2], fq, m1)); sc[i][3] = ex2(fmaf(sc[i][3], fq, m1));
        l0 += sc[i][0] + sc[i][1]; l1 += sc[i][2] + sc[i][3];
    }
#pragma unroll
    for (int o = 1; o < 4; o <<= 1) { l0 += __shfl_xor_sync(~0u, l0, o); l1 += __shfl_xor_sync(~0u, l1, o); }
    l0 = rcp(l0); l1 = rcp(l1);
#pragma unroll
    for (int i = 0; i < 5; i++) { pl[i] = pack_bf16(sc[i][0] * l0, sc[i][1] * l0); ph[i] = pack_bf16(sc[i][2] * l1, sc[i][3] * l1); }
    half();
    uint4 v[4][4];
    uint2 vm[4][2];
    auto fetch = [&](int n) {
        v[n][1] = lds128(vt + n * 512 + up * 2048); v[n][3] = lds128(vt + 4096 + n * 512 + up * 2048);
        v[n][0] = v[n][2] = make_uint4(0, 0, 0, 0);
        if (up) { v[n][0] = lds128(vt + n * 512); v[n][2] = lds128(vt + 4096 + n * 512); }
        vm[n][0] = lds64(kmr + 2048 + n * 256); vm[n][1] = lds64(kmr + 3072 + n * 256);
    };
    fetch(0);
#pragma unroll
    for (int n = 0; n < 4; n++) {
        if (n < 3) fetch(n + 1);
        float o[4][4];
#pragma unroll
        for (int i = 0; i < 4; i++) o[i][0] = o[i][1] = o[i][2] = o[i][3] = 0;
        mma16816(o[0], v[n][1], pl[3], pl[4]); mma16816(o[1], v[n][3], pl[3], pl[4]); mma16816(o[2], v[n][1], ph[3], ph[4]); mma16816(o[3], v[n][3], ph[3], ph[4]);
        if (up) { mma16816(o[0], v[n][0], pl[1], pl[2]); mma16816(o[1], v[n][2], pl[1], pl[2]); mma16816(o[2], v[n][0], ph[1], ph[2]); mma16816(o[3], v[n][2], ph[1], ph[2]); }
        mma1688(o[0], vm[n][0].x, vm[n][0].y, pl[0]); mma1688(o[1], vm[n][1].x, vm[n][1].y, pl[0]); mma1688(o[2], vm[n][0].x, vm[n][0].y, ph[0]); mma1688(o[3], vm[n][1].x, vm[n][1].y, ph[0]);
        const uint32_t d = out + (n >> 1) * 2048 + (n & 1) * 512;
        stsm4t(d, pack_bf16(o[0][0], o[0][1]), pack_bf16(o[0][2], o[0][3]), pack_bf16(o[1][0], o[1][1]), pack_bf16(o[1][2], o[1][3]));
        stsm4t(d + 1024, pack_bf16(o[2][0], o[2][1]), pack_bf16(o[2][2], o[2][3]), pack_bf16(o[3][0], o[3][1]), pack_bf16(o[3][2], o[3][3]));
    }
}
__device__ __forceinline__ void vs_attention(uint32_t sb, int h, int par, int up, int lane) {
    const uint32_t rec = sb + SM_AT + par * REC_BYTES, bar = sb + MB_AT + par * 8, out = sb + SM_AO0 + par * (SM_AO1 - SM_AO0);
    auto wait_step = [&](uint32_t v) { uint32_t n = 0; while (lds32(sb + SM_PH) < v) { spin_guard(++n); __nanosleep(ATT_NAP); } };
    const uint32_t epoch = *(volatile uint32_t*)&g_epoch;
    auto wait_record = [&](int g) {
        const uint32_t tag = epoch * NSEG + 1 + g;
        const uint32_t* p = lane == 0 ? g_flags[epoch & 1] + F_Q + (g >> 2) : g_fkt + h * 8 + (g == NSEG - 1 ? 2 : 0) + ((lane - 1) & 1);
        uint32_t n = 0;
        while (true) {
            const uint32_t x = ld_acquire(p);
            if (__all_sync(~0u, lane == 0 ? x >= 32 : (int)(x - tag) >= 0)) break;
            spin_guard(++n); __nanosleep(PUB_NAP);
        }
        fence_async();
    };
    auto request = [&](int g) {
        asm volatile("{.reg .pred p; elect.sync _|p, 0xffffffff;\n@p mbarrier.arrive.expect_tx.shared::cta.b64 _, [%2], %3;\n"
                     "@p cp.async.bulk.shared::cluster.global.mbarrier::complete_tx::bytes [%0], [%1], %3, [%2];}" :: "r"(rec), "l"(rec_ptr(h, g)), "r"(bar), "n"(REC_BYTES) : "memory");
        VT(g, 1);
    };
    auto announce = [&](int g) {
        if (lane < 4) { bulk_wait_all(); fence_async(); fence_release(); }
        __syncwarp();
        red_add_if(g_flags[epoch & 1] + F_ATT + (g >> 1), 1, lane == 0);
        VT(g, 7);
    };
    int next = 0;
#pragma unroll 1
    for (int s = par; s < NSEG; s += 2) {
        const bool late = s < ATT_EAGER;
        if (!up && next < 2) {
            if (late) wait_step(2 * s + ATT_REQ);
            if (!next) wait_record(s);
            request(s);
        }
        if (late) wait_step(2 * s + ATT_H1);
        if (up && s >= 2 && late) announce(s - 2);
        mbar_wait(bar, (s >> 1) & 1);
        mbar_wait(sb + MB_KM + (s & 7) * 8, (s >> 3) & 1);
        VT(s, up ? 5 : 3);
        att_pass(rec, out + up * 4096 + lane * 16, sb + SM_VR + (s % NVR) * 8192 + lane * 16, sb + SM_KM + (s % NKM) * 4096 + lane * 8, up, lane, [&] {
            next = late;
            if (late) { wait_step(2 * s + ATT_H2); if (!up) wait_record(s + 2); }
            bar_sync(2 + par, 64);
            if (late && !up && lds32(sb + SM_PH) >= 2 * s + 4 + ATT_REQ) { request(s + 2); next = 2; }
        });
        fence_async_smem();
        bar_sync(par, 64);
        VT(s, up ? 6 : 4);
        if (up) {
            sts32_if(sb + SM_AD + par * 4, (s >> 1) + 1, lane == 0);
            if (late) wait_step(2 * s + ATT_FLAG);
            uint32_t* dst = g_ox + (((s >> 1) * 64 + 2 * h) * 8 + par * 4) * 256;
            if (lane < 4) bulk_s2g(dst + (lane >> 1) * 512 + (lane & 1) * 2048, out + lane * 2048, 2048);
            if (s + 2 >= ATT_EAGER) announce(s);
            __syncwarp();
        }
    }
}

template <bool VS>
__device__ __forceinline__ void chain_aux(uint32_t sb, int cta, int h, int j, int w, int lane, const Maps* maps, const Ptrs* P) {
    if (w == 0) {
        if (lane == 0) {
            { const uint32_t c0 = clock(); while ((uint32_t)clock() - c0 < (uint32_t)START_DELAY) {} }
            if (PF_MODE) {
                const int c96 = cta_now();
#pragma unroll 1
                for (int i = 0; i < 27; i++) {
                    const int r = i * 96 + c96;
                    if (r < 2560) bulk_prefetch(reinterpret_cast<const unsigned char*>(r < 640 ? P->wo : r < 1280 ? P->wk : r < 1920 ? P->wv : P->wq) + (r % 640) * 8192, 8192);
                    if (PF_NAP) { const uint32_t c0 = clock(); while ((uint32_t)clock() - c0 < (uint32_t)PF_NAP) {} }
                }
            }
            if (!VS) {
                const int ec = h * DH + 64 * j;
#pragma unroll 1
                for (int n = -5; n < 8; n++) {
                    const int m = n - W_DEPTH;
                    if (m >= -5) mbar_wait(sb + (m < 0 ? MB_PO + (m + 5) * 8 : MB_PF + m * 8), 0);
                    if (n >= 5) mbar_wait(sb + MB_PE + (n == 7 ? 8 : 0), 0);
                    const uint32_t bar = sb + (n < 0 ? MB_PO + (n + 5) * 8 : MB_PF + n * 8);
                    mbar_arrive_tx(bar, n < 0 ? 16384 : 20480);
                    if (n < 0) tma2d(sb + STG_O + (n + 5) * 16384, &maps->o, 64 * (((j ? 0x87943 : 0x65210) >> (4 * n + 20)) & 15), h * DH, bar);
                    else tma2d(sb + STG_QK + (n % 5) * 20480, (n & 4) ? &maps->q : &maps->k, ec, 160 * (n & 3), bar);
                    if (n >= 2 && n < 5) tma2d_prefetch(&maps->q, ec, 160 * (n - 1));
                }
            } else {
#pragma unroll 1
                for (int n = 0; n < 8; n++) {
                    const int m = n - W_DEPTH_V, c = (n & 1) | (n & 2) << 1 | (n & 4) >> 1;
                    if (m >= 0) mbar_wait(sb + MB_PF + ((m & 1) | (m & 2) << 1 | (m & 4) >> 1) * 8, 0);
                    mbar_arrive_tx(sb + MB_PF + c * 8, 20480);
                    tma2d(sb + STG_V + c * 20480, &maps->v, h * DH + 64 * (c >> 2), 160 * (c & 3), sb + MB_PF + c * 8);
                }
            }
            if (VS) {
                wait_flag(launch_flags() + F_LN0, 128);
                fence_async();
                mbar_wait(sb + MB_L0 + 8, 0);
                mbar_arrive_tx(sb + MB_XN, 40960);
                tma3d(sb + SM_XN, &maps->xnp, 0, 0, 0, sb + MB_XN);
                mbar_wait(sb + MB_GO, 0);
                mbar_arrive_tx(sb + MB_XN2, 40960);
                tma3d(sb + SM_XN2, &maps->xnp, 0, 32, 0, sb + MB_XN2);
                mbar_wait(sb + MB_XNF, 0);
                mbar_arrive_tx(sb + MB_XN, 40960);
                tma3d(sb + SM_XN, &maps->xnp, 0, 64, 0, sb + MB_XN);
            }
        }
    }
    if (!VS && w == 0) {
        __syncwarp();
        constexpr uint32_t rv = SM_BASE + 2 * SM_RANK;
        mbar_arrive_tx_if(sb + MB_VX, 8192, lane == 0);
#pragma unroll 1
        for (int s = 0;; s++) {
            const uint32_t ph = s & 1;
            if (s < NSEG - 1) mbar_wait(sb + MB_VX, ph);
            mbar_arrive_tx_if(sb + MB_S + lane * 8, lane == 0 ? 1280 : lane == 1 ? 2048 : 8192, lane < (s < NSEG - 2 ? 3 : 2));
            bar_arrive(BAR_RED, 192);
            if (s == NSEG - 1) break;
            if (s) mbar_wait(sb + MB_MEM, ph ^ 1);
            const uint32_t own = post_time(h, j, s + 1, 0, lane == 0);
            wait_clk(clk(), SIG_POLL);
            const int lead = lead_time(h, own, lane);
            sts32(sb + SM_USC + lane * 8 + 4, lead);
            if (j == 0 && lane == 0) st_async32(rv + SM_RC + 8, lead, rv + MB_R);
            __syncwarp();
            mbar_wait(sb + MB_XN, ph);
            mbar_wait(sb + MB_KTF, ph ^ 1);
            bar_sync(BAR_PW, 288);
        }
    } else if (!VS && w == 3) {
        wait_flag(launch_flags() + F_LN0, 128);
        mbar_wait(sb + MB_L0 + 8, 0);
        float usc = pow2i(-(int)lds32(sb + SM_CST));
#pragma unroll 1
        for (int g = 0; g <= NSEG; g++) {
            if (g) mbar_wait(sb + MB_XNF, (g - 1) & 1);
            if (g == 0 || g == 3) fence_async();
            if (g >= 3) mbar_wait(sb + MB_MEM, (g - 1) & 1);
            tma_xn(sb + SM_XN, &maps->xnp, min(g, NSEG - 1), sb + MB_XN);
            if (g < 2) continue;
            if (g == 2) mbar_wait(sb + MB_CST, 0);
            usc = pow2i(-out_scale(sb, usc, lane));
            sts32(sb + SM_USC + lane * 8, __float_as_uint(usc));
            wait_count(sb + SM_CST + 44, max(g - 3, 0));
            bar_sync(BAR_O, 288);
            sfence(P->zero);
            constexpr uint32_t rv = SM_BASE + 2 * SM_RANK;
            st_async64_if(rv + SM_RC, clk() + (POLL_EARLY - V_LEAD), __float_as_uint(usc), rv + MB_R, j == 0 && lane == 0);
        }
    } else if (w == 1) {
        if (lane == 0) {
            if (cta_now() < 16) { mbar_wait(sb + MB_L0, 0); __threadfence(); atomicAdd(launch_flags() + F_LN0, 8); }
            mbar_wait(sb + MB_L0 + 8, 0); __threadfence(); atomicAdd(launch_flags() + F_LN, 8);
            const uint32_t tag0 = launch_tag();
#pragma unroll 1
            for (int s = 0; s < (VS ? 0 : NSEG); s++) {
                mbar_wait(sb + MB_KT, s & 1);
                fence_async_smem();
                bulk_s2g(rec_ptr(h, s) + REC_K + j * 4096, sb + ((s & 1) ? SM_KT1 : SM_KT0), 4096);
                asm volatile("cp.async.bulk.wait_group.read 0;" ::: "memory");
                mbar_arrive(sb + MB_KTF);
                bulk_wait_all();
                if (s < NSEG - 1) { sts32(sb + SM_CST + 40, s + 1); continue; }
                fence_async(); __threadfence();
                st_relaxed32(g_fkt + h * 8 + 2 + j, tag0 + s);
            }
        }
    } else if (w == 2) {
        unsigned char* z = g_ring + ring_pos(cta) + lane * 16;
        uint32_t* fl = launch_flags();
        if (!VS && lane < 16) st_relaxed128(z + 32768, make_uint4(0, 0, 0, 0));
        __syncwarp();
        if (lane == 0) {
            mbar_wait(sb + MB_OM, 0);
            if (TRIG == 2) asm volatile("griddepcontrol.launch_dependents;");
            __threadfence();
            flag_add(fl + F_INIT);
            wait_flag(fl + F_INIT, LN_CTAS);
            const float wv = __uint_as_float(ld_relaxed32(fl + F_WV)), wo = __uint_as_float(ld_relaxed32(fl + F_WO));
            sts64(sb + SM_CST + 32, __float_as_uint(wv * wo * (1.02f * 4096.0f * 25.3f)), ld_relaxed32(fl + F_XN));
            if (VS) fence_async();
            mbar_arrive(sb + MB_CST);
        }
        __syncwarp();
        if (!VS) {
            const uint32_t tag0 = launch_tag();
#pragma unroll 1
            for (int s = 0; s < NSEG; s++) {
                mbar_wait(sb + MB_PUB + (s & 1) * 8, (s >> 1) & 1);
                if (lane == 0 && s == 0) GT(1);
                if (lane == 0 && s == NSEG - 1) GT(2);
                if (s < NSEG - 1 && PUB_LATE) mbar_wait(sb + MB_MEM, s & 1);
                const int zs = (s + 3) & 3;
                if (lane < 16 && s < NSEG - 1) st_relaxed128(z + (zs & 1) * 512 + (zs >> 1) * 32768, make_uint4(0, 0, 0, 0));
                if (s == NSEG - 1) break;
                { uint32_t n = 0; while (lds32(sb + SM_CST + 40) <= (uint32_t)min(s + 1, NSEG - 2)) { spin_guard(++n); __nanosleep(100); } }
                fence_async();
                __threadfence();
                __syncwarp();
                if (lane == 0) {
                    st_relaxed32(g_fkt + h * 8 + j, tag0 + min(s + 1, NSEG - 2));
                    asm volatile("st.release.cta.shared.u32 [%0], %1;" :: "r"(sb + SM_CST + 44), "r"(s + 1) : "memory");
                }
            }
        }
    }
    if (VS) { __syncwarp(); const int ww = __reduce_max_sync(~0u, w); vs_attention(sb, h, ww & 1, ww >> 1, lane); }
}

constexpr int NG = 36;
constexpr int GS_Q = 49152;
constexpr int GS_OA = 163840;
constexpr int GB_QF = SM_BAR, GB_QE = SM_BAR + 32, GB_OF = SM_PROF, GB_OE = SM_PROF + 64, GB_WO = SM_BAR + 128, GB_QD = SM_BAR + 136;
constexpr int G_SEL = SM_CST, G_RS = SM_BAR + 160;
constexpr int G_Q = SM_BAR + 256, GB_ML = SM_BAR + 144;
constexpr int BAR_G = 1, BAR_W = 2;

__device__ __forceinline__ uint4 ldcg128(const void* p) { uint4 v; asm volatile("ld.global.cg.v4.u32 {%0,%1,%2,%3}, [%4];" : "=r"(v.x), "=r"(v.y), "=r"(v.z), "=r"(v.w) : "l"(p)); return v; }
__device__ __forceinline__ uint2 ldcg64(const void* p) { uint2 v; asm volatile("ld.global.cg.v2.u32 {%0,%1}, [%2];" : "=r"(v.x), "=r"(v.y) : "l"(p)); return v; }
__device__ __forceinline__ uint4 ld128(const void* p) { uint4 v; asm volatile("ld.global.v4.u32 {%0,%1,%2,%3}, [%4];" : "=r"(v.x), "=r"(v.y), "=r"(v.z), "=r"(v.w) : "l"(p) : "memory"); return v; }
__device__ __forceinline__ uint2 ld64(const void* p) { uint2 v; asm volatile("ld.global.v2.u32 {%0,%1}, [%2];" : "=r"(v.x), "=r"(v.y) : "l"(p) : "memory"); return v; }
__device__ __forceinline__ float bflo(uint32_t w) { return __uint_as_float(w << 16); }
__device__ __forceinline__ float bfhi(uint32_t w) { return __uint_as_float(w & 0xffff0000u); }
__device__ __forceinline__ float sigmoidf_(float x) { return __fdividef(1.0f, 1.0f + __expf(-x)); }
#define R8(c, i) "+f"(c[i]), "+f"(c[i + 1]), "+f"(c[i + 2]), "+f"(c[i + 3]), "+f"(c[i + 4]), "+f"(c[i + 5]), "+f"(c[i + 6]), "+f"(c[i + 7])
__device__ __forceinline__ void wgmma_n256(float (&c)[128], uint64_t a, uint64_t b, uint32_t acc) {
    asm volatile("{.reg .pred p; setp.ne.u32 p, %130, 0;\n"
        "wgmma.mma_async.sync.aligned.m64n256k16.f32.bf16.bf16 {%0,%1,%2,%3,%4,%5,%6,%7,%8,%9,%10,%11,%12,%13,%14,%15,%16,%17,%18,%19,%20,%21,%22,%23,%24,%25,%26,%27,%28,%29,%30,%31,"
        "%32,%33,%34,%35,%36,%37,%38,%39,%40,%41,%42,%43,%44,%45,%46,%47,%48,%49,%50,%51,%52,%53,%54,%55,%56,%57,%58,%59,%60,%61,%62,%63,"
        "%64,%65,%66,%67,%68,%69,%70,%71,%72,%73,%74,%75,%76,%77,%78,%79,%80,%81,%82,%83,%84,%85,%86,%87,%88,%89,%90,%91,%92,%93,%94,%95,"
        "%96,%97,%98,%99,%100,%101,%102,%103,%104,%105,%106,%107,%108,%109,%110,%111,%112,%113,%114,%115,%116,%117,%118,%119,%120,%121,%122,%123,%124,%125,%126,%127},%128,%129,p,1,1,0,1;}"
        : R8(c, 0), R8(c, 8), R8(c, 16), R8(c, 24), R8(c, 32), R8(c, 40), R8(c, 48), R8(c, 56), R8(c, 64), R8(c, 72), R8(c, 80), R8(c, 88), R8(c, 96), R8(c, 104), R8(c, 112), R8(c, 120)
        : "l"(a), "l"(b), "r"(acc));
}
__device__ __forceinline__ void wgmma_n128(float (&c)[64], uint64_t a, uint64_t b, uint32_t acc) {
    asm volatile("{.reg .pred p; setp.ne.u32 p, %66, 0;\n"
        "wgmma.mma_async.sync.aligned.m64n128k16.f32.bf16.bf16 {%0,%1,%2,%3,%4,%5,%6,%7,%8,%9,%10,%11,%12,%13,%14,%15,%16,%17,%18,%19,%20,%21,%22,%23,%24,%25,%26,%27,%28,%29,%30,%31,"
        "%32,%33,%34,%35,%36,%37,%38,%39,%40,%41,%42,%43,%44,%45,%46,%47,%48,%49,%50,%51,%52,%53,%54,%55,%56,%57,%58,%59,%60,%61,%62,%63},%64,%65,p,1,1,0,1;}"
        : R8(c, 0), R8(c, 8), R8(c, 16), R8(c, 24), R8(c, 32), R8(c, 40), R8(c, 48), R8(c, 56)
        : "l"(a), "l"(b), "r"(acc));
}
__device__ __forceinline__ void wg_done(uint32_t sb, int wg, uint32_t& nq, uint32_t flag, int tid) {
    bar_sync(BAR_W + wg, 128);
    if ((tid & 127) == 0) {
        uint32_t n = 0;
        while (nq - lds64(sb + G_Q + wg * 32).y >= 4) spin_guard(++n >> 4);
        sts32(sb + G_Q + wg * 32 + 16 + (nq & 3) * 4, flag);
        asm volatile("st.release.cta.shared.u32 [%0], %1;" :: "r"(sb + G_Q + wg * 32), "r"(nq + 1) : "memory");
    }
    nq++;
}
__device__ __forceinline__ void gemm_publisher(uint32_t sb, int lane) {
    uint32_t* fl = launch_flags();
    const uint32_t q = sb + G_Q + (lane & 1) * 32;
    uint32_t head = 0, n = 0;
    bool done = lane >= 2;
    while (!__all_sync(~0u, done)) {
        uint32_t tail;
        asm volatile("ld.acquire.cta.shared.u32 %0, [%1];" : "=r"(tail) : "r"(q) : "memory");
        if (done) tail = head;
        if (!__any_sync(~0u, tail != head)) { spin_guard(++n >> 2); __nanosleep(30); continue; }
        n = 0;
        __threadfence();
        for (; head != tail; head++) {
            const uint2 e = lds64(q + 16 + (head & 2) * 4);
            const uint32_t f = (head & 1) ? e.y : e.x;
            if (f == ~0u) done = true; else atomicAdd(fl + f, 1);
        }
        if (lane < 2) sts32(q + 4, head);
        __syncwarp();
    }
}

__device__ __forceinline__ float warp_sum(float v) {
#pragma unroll
    for (int o = 16; o; o >>= 1) v += __shfl_xor_sync(~0u, v, o);
    return v;
}
__device__ __forceinline__ void g_select(uint32_t tmp, uint32_t sb, int tid) {
    const int lane = tid & 31, warp = tid >> 5;
    uint32_t key[8];
#pragma unroll
    for (int i = 0; i < 8; i++) {
        const int tok = tid + 256 * i;
        const uint32_t b = __float_as_uint(__ldcg(g_r + tok) + 0.0f) >> 16;
        key[i] = (((b & 0x8000u) ? (~b & 0xffffu) : (b | 0x8000u)) << 16) | (uint32_t)(S_TOK - 1 - tok);
    }
    auto pick = [&](uint32_t* k, int n, uint32_t dst) {
        for (int c = 0; c < 8; c++) {
            uint32_t m = 0;
#pragma unroll
            for (int i = 0; i < 8; i++) if (i < n) m = max(m, k[i]);
            m = __reduce_max_sync(~0u, m);
#pragma unroll
            for (int i = 0; i < 8; i++) if (i < n && k[i] == m) k[i] = 0;
            if (lane == 0) sts32(dst + c * 4, m);
        }
    };
    pick(key, 8, tmp + warp * 32);
    bar_sync(BAR_G, 256);
    if (warp == 0) {
        const uint2 x = lds64(tmp + lane * 8);
        key[0] = x.x; key[1] = x.y;
        pick(key, 2, sb + G_SEL);
        __syncwarp();
        if (lane < 8) {
            const int tok = S_TOK - 1 - (int)(lds64(sb + G_SEL + (lane & ~1) * 4).x * (1 - (lane & 1)) + lds64(sb + G_SEL + (lane & ~1) * 4).y * (lane & 1) & 0xffffu);
            __syncwarp(0xff);
            sts32(sb + G_SEL + lane * 4, tok);
            sts32(sb + G_RS + lane * 4, __float_as_uint(bf16_round(sigmoidf_(__ldcg(g_r + tok)))));
        }
    }
    bar_sync(BAR_G, 256);
}

__device__ __forceinline__ void g_mlp(uint32_t sb, int part, int tid) {
    const int warp = tid >> 5, lane = tid & 31, m = lane >> 3, sg = lane & 7, r = lane >> 2, jj = lane & 3;
    const uint32_t xs = sb + 163840, hs = xs + 10240, gs = hs + 1024;
    const uint32_t tok = lds64(sb + G_SEL + (r & ~1) * 4 ).x * (1 - (r & 1)) + lds64(sb + G_SEL + (r & ~1) * 4).y * (r & 1);
#pragma unroll 1
    for (int k = warp; k < 40; k += 8) {
        const uint32_t* p = reinterpret_cast<const uint32_t*>(g_xn + tok * DM + 16 * k + 2 * jj);
        sts64(xs + k * 256 + lane * 8, __ldcg(p), __ldcg(p + 4));
    }
    bar_sync(BAR_G, 256);
    mbar_wait(sb + GB_ML, 0);
    float a[4] = {0, 0, 0, 0};
    {
        const uint32_t base = sb + (warp >> 2) * 81920 + (8 * (m >> 1) + sg) * 128 + (((2 * (warp & 3) + (m & 1)) ^ sg) << 4);
#pragma unroll 4
        for (int k = 0; k < 40; k++) { const uint2 b = lds64(xs + k * 256 + lane * 8); mma16816(a, ldsm4t(base + k * 2048), b.x, b.y); }
    }
    if (warp < 4) {
#pragma unroll
        for (int i = 0; i < 4; i++) { const float g = bf16_round(a[i]); a[i] = bf16_round(g * sigmoidf_(g)); }
        sts128f(gs + tid * 16, a[0], a[1], a[2], a[3]);
    }
    bar_sync(BAR_G, 256);
    if (tid == 0) mbar_arrive(sb + GB_QD);
    if (warp >= 4) {
        const uint4 g = lds128(gs + (tid - 128) * 16);
        sts64(hs + (warp - 4) * 256 + lane * 8, movmat(pack_bf16(__uint_as_float(g.x) * bf16_round(a[0]), __uint_as_float(g.y) * bf16_round(a[1]))),
              movmat(pack_bf16(__uint_as_float(g.z) * bf16_round(a[2]), __uint_as_float(g.w) * bf16_round(a[3]))));
    }
    bar_sync(BAR_G, 256);
    mbar_wait(sb + GB_ML, 1);
#pragma unroll 1
    for (int tile = warp; tile < 40; tile += 8) {
        const uint32_t base = sb + (tile >> 2) * 8192 + (8 * (m >> 1) + sg) * 128 + (((2 * (tile & 3) + (m & 1)) ^ sg) << 4);
        float y[4] = {0, 0, 0, 0};
#pragma unroll
        for (int k = 0; k < 4; k++) { const uint2 b = lds64(hs + k * 256 + lane * 8); mma16816(y, ldsm4t(base + k * 2048), b.x, b.y); }
        float* dst = g_y + (part * 8 + 2 * jj) * DM + 16 * tile + r;
        dst[0] = y[0]; dst[DM] = y[1]; dst[8] = y[2]; dst[DM + 8] = y[3];
    }
}

__device__ __forceinline__ void quad_transpose(uint32_t (&w)[4], int lane) {
    const bool o1 = lane & 1, o2 = lane & 2;
    uint32_t a = __shfl_xor_sync(~0u, o1 ? w[0] : w[1], 1), b = __shfl_xor_sync(~0u, o1 ? w[2] : w[3], 1);
    if (o1) { w[0] = a; w[2] = b; } else { w[1] = a; w[3] = b; }
    a = __shfl_xor_sync(~0u, o2 ? w[0] : w[2], 2); b = __shfl_xor_sync(~0u, o2 ? w[1] : w[3], 2);
    if (o2) { w[0] = a; w[1] = b; } else { w[2] = a; w[3] = b; }
}
__device__ __forceinline__ void g_epilogue(const Ptrs& P, uint32_t sb, int u, int tile, int lane) {
    const uint4* part = g_part + (u % 6) * (7 * 64 * DM / 8) + tile * 64 + lane;
    const uint32_t tok = u * 64 + ((tile >> 2) & 3) * 16 + (lane >> 2), col = (tile >> 4) * 128 + (tile & 3) * 32 + (lane & 3) * 8;
    uint4 p[7][2], xw[2], nw[2];
#pragma unroll
    for (int k = 0; k < 7; k++)
#pragma unroll
        for (int g = 0; g < 2; g++) p[k][g] = ld128(part + k * (64 * DM / 8) + g * 32);
#pragma unroll
    for (int u = 0; u < 2; u++) { xw[u] = ld128(P.x + (tok + 8 * u) * DM + col); nw[u] = ld128(g_xn + (tok + 8 * u) * DM + col); }
    const uint4 s0 = lds128(sb + G_SEL), s1 = lds128(sb + G_SEL + 16);
    uint32_t sw[2][4];
#pragma unroll
    for (int g = 0; g < 4; g++) {
        float v[4] = {0, 0, 0, 0};
#pragma unroll
        for (int k = 0; k < 7; k++) {
            const uint32_t a = (g & 1) ? p[k][g >> 1].z : p[k][g >> 1].x, b = (g & 1) ? p[k][g >> 1].w : p[k][g >> 1].y;
            v[0] += bflo(a); v[1] += bfhi(a); v[2] += bflo(b); v[3] += bfhi(b);
        }
        sw[0][g] = pack_bf16(v[0], v[1]); sw[1][g] = pack_bf16(v[2], v[3]);
    }
#pragma unroll
    for (int u = 0; u < 2; u++) {
        quad_transpose(sw[u], lane);
        const uint32_t t = tok + 8 * u;
        uint32_t gw[4] = {nw[u].x, nw[u].y, nw[u].z, nw[u].w};
        const uint32_t xx[4] = {xw[u].x, xw[u].y, xw[u].z, xw[u].w};
        const int k = s0.x == t ? 0 : s0.y == t ? 1 : s0.z == t ? 2 : s0.w == t ? 3 : s1.x == t ? 4 : s1.y == t ? 5 : s1.z == t ? 6 : s1.w == t ? 7 : -1;
        if (k >= 0) {
            const uint4 y0 = ld128(g_yf + k * DM + col), y1 = ld128(g_yf + k * DM + col + 4);
            gw[0] = pack_bf16(bflo(gw[0]) + __uint_as_float(y0.x), bfhi(gw[0]) + __uint_as_float(y0.y));
            gw[1] = pack_bf16(bflo(gw[1]) + __uint_as_float(y0.z), bfhi(gw[1]) + __uint_as_float(y0.w));
            gw[2] = pack_bf16(bflo(gw[2]) + __uint_as_float(y1.x), bfhi(gw[2]) + __uint_as_float(y1.y));
            gw[3] = pack_bf16(bflo(gw[3]) + __uint_as_float(y1.z), bfhi(gw[3]) + __uint_as_float(y1.w));
        }
        uint32_t o[4];
#pragma unroll
        for (int i = 0; i < 4; i++) {
            const uint32_t gt = pack_bf16(bflo(gw[i]) * sigmoidf_(bflo(gw[i])), bfhi(gw[i]) * sigmoidf_(bfhi(gw[i])));
            const uint32_t pr = pack_bf16(bflo(sw[u][i]) * bflo(gt), bfhi(sw[u][i]) * bfhi(gt));
            o[i] = pack_bf16(bflo(xx[i]) + bflo(pr), bfhi(xx[i]) + bfhi(pr));
        }
        *reinterpret_cast<uint4*>(P.out + t * DM + col) = make_uint4(o[0], o[1], o[2], o[3]);
    }
}

struct OSlice {
    int nt, ks, nkb, kb0; bool on;
    __device__ __forceinline__ OSlice(int c) { const int o = c < 4 ? c + 32 : c - 4; ks = o / 5; nt = o - 5 * ks; on = o < 35; nkb = ks ? 9 : 10; kb0 = ks ? 1 + 9 * ks : 0; }
};
__device__ __forceinline__ bool wg_all(int id, bool x) {
    uint32_t r;
    asm volatile("{.reg .pred p, q; setp.ne.u32 p, %2, 0; barrier.red.and.pred q, %1, 128, p; selp.u32 %0, 1, 0, q;}" : "=r"(r) : "r"(id), "r"((uint32_t)x) : "memory");
    return r;
}
template <int wg>
__device__ __forceinline__ uint32_t gemm_tail(const Ptrs& P, uint32_t sb, int c, int tid, uint32_t nq) {
    const int warp = tid >> 5, lane = tid & 31;
    const uint32_t* fl = launch_flags();
    if (wg == 0) {
        const OSlice os(c);
        if (!os.on) return nq;
        wg_fence(); wg_commit(); wg_fence(); wg_commit(); wg_wait<0>();
        mbar_wait(sb + GB_WO, 0);
        uint32_t it = 0, ne = 0, pw[32];
        bool pending = false;
        const bool ten = __reduce_max_sync(~0u, os.nkb) == 10;
        auto store = [&](int u) {
            if (u >= 6 && __any_sync(~0u, ne < 80)) { uint32_t n = 0; while (__any_sync(~0u, ld_relaxed32(fl + F_EPI + u - 6) < 80)) { spin_guard(++n); __nanosleep(100); } }
            uint4* dst = g_part + ((u % 6) * 7 + os.ks) * (64 * DM / 8) + (os.nt * 4 + warp) * 256 + lane;
#pragma unroll
            for (int g = 0; g < 8; g++) dst[g * 32] = make_uint4(pw[4 * g], pw[4 * g + 1], pw[4 * g + 2], pw[4 * g + 3]);
            wg_done(sb, 0, nq, F_O + u, tid);
        };
#pragma unroll 1
        for (int u = 0; u < 32; u++) {
            float acc[64];
            const uint32_t i0 = __reduce_max_sync(~0u, it);
            const uint64_t b0 = P.desc_b + (i0 & P.zero);
#pragma unroll
            for (int i = 0; i < 10; i++) {
                if (i == 9 && !ten) break;
                const uint32_t st = (i0 + i) & 7;
                mbar_wait(sb + GB_OF + st * 8, ((i0 + i) >> 3) & 1);
                const uint64_t alo = P.desc_oa + ((SM_BASE + GS_OA) >> 4) + st * 512, blo = b0 + ((SM_BASE + i * 16384) >> 4);
                wg_fence();
#pragma unroll
                for (int k = 0; k < 4; k++) wgmma_n128(acc, alo + k * 16, blo + k * 128, i | k);
                wg_commit();
                if (i == 2 && pending) store(u - 1);
                if (i == 6) ne = ld_relaxed32(fl + F_EPI + max(u - 6, 0));
                if (i > 1) { wg_wait<2>(); mbar_arrive_if(sb + GB_OE + ((i0 + i + 6) & 7) * 8, lane == 0); }
            }
            it += os.nkb;
            pending = wg_all(BAR_W, u < 31 && mbar_try(sb + GB_OF + (it & 7) * 8, (it >> 3) & 1));
            wg_wait<0>();
            mbar_arrive_if(sb + GB_OE + ((it + 6 + (lane & 1)) & 7) * 8, lane < 2);
#pragma unroll
            for (int g = 0; g < 32; g++) pw[g] = pack_bf16(acc[2 * g], acc[2 * g + 1]);
            if (!pending) store(u);
        }
    } else {
        if (c < 20) {
            if (tid == 128) wait_flag(fl + F_MOD, 54);
            bar_sync(BAR_W + 1, 128);
            if (tid < 192) {
                const int i = c * 64 + tid - 128;
                float y[4] = {0, 0, 0, 0};
#pragma unroll
                for (int q = 0; q < 27; q++) {
                    const uint4 w = ldcg128(g_y + q * (8 * DM) + i * 4);
                    y[0] += __uint_as_float(w.x); y[1] += __uint_as_float(w.y); y[2] += __uint_as_float(w.z); y[3] += __uint_as_float(w.w);
                }
                const uint2 rw = lds64(sb + G_RS + ((i / 160) & ~1) * 4);
                const float rs = __uint_as_float(((i / 160) & 1) ? rw.y : rw.x);
                *reinterpret_cast<float4*>(g_yf + i * 4) = make_float4(bf16_round(bf16_round(y[0]) * rs), bf16_round(bf16_round(y[1]) * rs), bf16_round(bf16_round(y[2]) * rs), bf16_round(bf16_round(y[3]) * rs));
            }
            wg_done(sb, 1, nq, F_YF, tid);
        }
        { uint32_t n = 0; while (__any_sync(~0u, ld_acquire(fl + F_YF) < 20)) { spin_guard(++n); __nanosleep(E_NAP); } }
#pragma unroll 1
        for (int g = (warp & 3) * NG + c; g < 32 * 80; g += 4 * NG) {
            const int u = g / 80;
            { uint32_t n = 0; while (__any_sync(~0u, ld_acquire(fl + F_O + u) < 35)) { spin_guard(++n); __nanosleep(u < 30 ? E_NAP : G_NAP); } }
            g_epilogue(P, sb, u, g - 80 * u, lane);
            __syncwarp();
            red_add_if(const_cast<uint32_t*>(fl) + F_EPI + u, 1, lane == 0);
        }
    }
    return nq;
}

template <int N> struct Int { static constexpr int value = N; };
__device__ __forceinline__ void gemm_main(unsigned char* smem, uint32_t sb, int c, int tid, const Ptrs& P) {
    const int warp = tid >> 5, lane = tid & 31, wg = __reduce_max_sync(~0u, tid >> 7);
    uint32_t* fl = launch_flags();
    if (c == 0) for (int i = tid; i < F_WORDS; i += 256) g_flags[(*(volatile uint32_t*)&g_epoch & 1) ^ 1][i] = 0;
    bar_sync(BAR_G, 256);
    if (tid == 0) { if (LN_CTAS > 96) { __threadfence(); flag_add(fl + F_INIT); } wait_flag(fl + F_LN, LN_WARPS); GT(1); }
    bar_sync(BAR_G, 256);
    if (tid == 0) mbar_arrive(sb + GB_QD);
    uint32_t nq = 0;
    if (tid == 0) GT(2);
    {
        float acc[128];
        uint32_t it = 0, pw[64];
        auto store = [&](int task, auto part) {
            constexpr int T0 = 4 * decltype(part)::value;
            uint4* dst = reinterpret_cast<uint4*>(rec_ptr(2 * (task & 15) + (T0 >> 3), 4 * (task >> 4) + (warp >> 1)) + REC_Q + (warp & 1) * 4096) + lane;
#pragma unroll
            for (int T = T0; T < T0 + 4; T++) dst[(T & 7) * 32] = make_uint4(pw[4 * T], pw[4 * T + 1], pw[4 * T + 2], pw[4 * T + 3]);
            if (T0 == 12) wg_done(sb, wg, nq, F_Q + (task >> 4), tid);
        };
#pragma unroll 1
        for (int task = c;; task += NG) {
#pragma unroll 1
            for (int kb = 0; kb < 10; kb++, it++) {
                const uint32_t st = it & 3;
                mbar_wait(sb + GB_QF + st * 8, (it >> 2) & 1);
                const uint32_t stu = __reduce_max_sync(~0u, st);
                const uint64_t alo = P.desc + ((SM_BASE + stu * GS_Q + wg * 8192) >> 4), blo = P.desc_b + ((SM_BASE + stu * GS_Q + 16384) >> 4);
                wg_fence();
#pragma unroll
                for (int k = 0; k < 4; k++) wgmma_n256(acc, alo + k * 2, blo + k * 128, kb | k);
                wg_commit();
                if (kb > 0) { wg_wait<1>(); mbar_arrive_if(sb + GB_QE + ((it - 1) & 3) * 8, lane == 0); }
                if (task >= 2 * NG) {
                    if (kb == 0) store(task - NG, Int<0>()); else if (kb == 1) store(task - NG, Int<1>());
                    else if (kb == 2) store(task - NG, Int<2>()); else if (kb == 3) store(task - NG, Int<3>());
                }
            }
            wg_wait<0>();
            mbar_arrive_if(sb + GB_QE + ((it - 1) & 3) * 8, lane == 0);
#pragma unroll
            for (int i = 0; i < 64; i++) pw[i] = pack_bf16(acc[2 * i], acc[2 * i + 1]);
            if (task + NG >= 256) {
                bar_sync(BAR_G, 256);
                if (tid == 0) mbar_arrive(sb + GB_QD);
            }
            if (task < NG || task + NG >= 256) { store(task, Int<0>()); store(task, Int<1>()); store(task, Int<2>()); store(task, Int<3>()); }
            if (task + NG >= 256) break;
        }
    }
    g_select(sb + SM_PROF + 256, sb, tid);
    if (c >= NG - 27) {
        g_mlp(sb, c - (NG - 27), tid);
        wg_done(sb, wg, nq, F_MOD, tid);
        bar_sync(BAR_G, 256);
        if (tid == 0) mbar_arrive(sb + GB_QD);
    }
    if (tid == 0) GT(3);
    if (wg == 0) nq = gemm_tail<0>(P, sb, c, tid, nq); else nq = gemm_tail<1>(P, sb, c, tid, nq);
    wg_done(sb, wg, nq, ~0u, tid);
    bar_sync(BAR_G, 256);
    if (tid == 128) GT(6);
    if (c == 0 && tid == 128) g_epoch = *(volatile uint32_t*)&g_epoch + 1;
}

__device__ __forceinline__ void gemm_producer(uint32_t sb, int c, const Maps* maps) {
    const OSlice os(c);
    const int nt = os.nt, nkb = os.nkb, kb0 = os.kb0;
    mbar_wait(sb + GB_QD, 0);
    fence_async();
    uint32_t it = 0;
#pragma unroll 1
    for (int task = c; task < 256; task += NG) {
#pragma unroll 1
        for (int kb = 0; kb < 10; kb++, it++) {
            const uint32_t st = it & 3, bar = sb + GB_QF + st * 8, dst = sb + st * GS_Q;
            if (it >= Q_DEPTH) mbar_wait(sb + GB_QE + ((it - Q_DEPTH) & 3) * 8, ((it - Q_DEPTH) >> 2) & 1);
            mbar_arrive_tx(bar, GS_Q);
            tma2d(dst, &maps->xn, 64 * kb, 128 * (task >> 4), bar);
            for (int i = 0; i < 4; i++) tma2d(dst + 16384 + i * 8192, &maps->q64, 256 * (task & 15) + 64 * i, 64 * kb, bar);
            const int pf = (int)it - PF_FROM;
            if (pf >= 0 && pf < 18 && c >= NG - 27) {
                if (pf < 8) tma2d_prefetch(pf < 4 ? &maps->wg : &maps->wu, (c - (NG - 27)) * 64, 160 * (pf & 3));
                else tma2d_prefetch(&maps->wd, 64 * (pf - 8), (c - (NG - 27)) * 64);
            }
            if (pf >= 10 && pf < 10 + 2 * nkb && os.on) tma2d_prefetch(&maps->o64, 128 * nt + 64 * (pf & 1), 64 * (kb0 + ((pf - 10) >> 1)));
        }
    }
    mbar_wait(sb + GB_QD, 1);
    if (c >= NG - 27) {
        const int f0 = (c - (NG - 27)) * 64;
        mbar_arrive_tx(sb + GB_ML, 163840);
#pragma unroll 1
        for (int i = 0; i < 8; i++) { tma2d(sb + i * 20480, i < 4 ? &maps->wg : &maps->wu, f0, 160 * (i & 3), sb + GB_ML); wait_clk(clk(), G_PACE * 5 / 2); }
        mbar_wait(sb + GB_QD, 0);
        mbar_arrive_tx(sb + GB_ML, 81920);
#pragma unroll 1
        for (int i = 0; i < 10; i++) { tma2d(sb + i * 8192, &maps->wd, 64 * i, f0, sb + GB_ML); wait_clk(clk(), G_PACE); }
        mbar_wait(sb + GB_QD, 1);
    }
    if (!os.on) return;
    mbar_arrive_tx(sb + GB_WO, nkb * 16384);
#pragma unroll 1
    for (int i = 0; i < 2 * nkb; i++) { tma2d(sb + i * 8192, &maps->o64, 128 * nt + 64 * (i & 1), 64 * (kb0 + (i >> 1)), sb + GB_WO); wait_clk(clk(), G_PACE); }
}
__device__ __forceinline__ void gemm_producer_o(uint32_t sb, int c, int me, int lane, const __nv_bfloat16* x) {
    const uint32_t* fl = launch_flags() + F_ATT + lane;
    const OSlice os(c);
    const int nst = os.on ? os.nkb : 0;
    const uint32_t* src = g_ox + os.kb0 * 2048;
    if (os.on) mbar_wait(sb + GB_WO, 0);
    int known = 0, i = me;
    uint32_t it = me;
#pragma unroll 1
    for (int u = 0; u < 32; u++) {
        if (u >= known) {
            uint32_t n = 0;
            while ((known = __clz(__brev(~__ballot_sync(~0u, ld_acquire(fl) >= 64)))) <= u) { spin_guard(++n); __nanosleep(G_NAP); }
            fence_async();
        }
#pragma unroll 1
        for (; i < nst; i += 3, it += 3) {
            const uint32_t st = it & 7, bar = sb + GB_OF + st * 8;
            if (it >= O_DEPTH) mbar_wait(sb + GB_OE + ((it - O_DEPTH) & 7) * 8, ((it - O_DEPTH) >> 3) & 1);
            asm volatile("{.reg .pred p; elect.sync _|p, 0xffffffff;\n@p mbarrier.arrive.expect_tx.shared::cta.b64 _, [%2], 8192;\n"
                         "@p cp.async.bulk.shared::cluster.global.mbarrier::complete_tx::bytes [%0], [%1], 8192, [%2];}" :: "r"(sb + GS_OA + st * 8192), "l"(src + (u * 64 + i) * 2048), "r"(bar) : "memory");
        }
        i -= nst;
        if (me < 2 && lane == 0) bulk_prefetch((me ? x : g_xn) + u * (64 * DM) + min(c * 1144, 64 * DM - 1144), 2288);
        __syncwarp();
    }
}

__device__ __forceinline__ void stg64_if(const void* p, uint32_t x, uint32_t y, bool c) {
    asm volatile("{.reg .pred p; setp.ne.u32 p, %3, 0; @p st.global.v2.u32 [%0], {%1, %2};}" :: "l"(p), "r"(x), "r"(y), "r"((uint32_t)c) : "memory");
}
__device__ __forceinline__ void layernorm_rows(const Ptrs& P, uint32_t sb, int gw, int lane) {
    const int warp = gw & 7, nrow = gw + 2 * LN_WARPS < S_TOK ? 3 : gw + LN_WARPS < S_TOK ? 2 : 1;
    const uint32_t rows = sb + SM_XN + warp * (4 * 1280), bar = sb + MB_LN + warp * 8;
    if (lane == 0) mbar_arrive_tx(bar, (nrow + 1) * 1280);
    __syncwarp();
    if (lane <= nrow) bulk_g2s(rows + lane * 1280, lane ? P.x + (gw + (lane - 1) * LN_WARPS) * DM : P.wr, 1280, bar);
    sts32(sb + SM_CST + warp * 4, mem0_exp(P.mem0, lane));
    uint32_t* fl = launch_flags();
    const bool up = lane & 2;
    int slot[5];
#pragma unroll
    for (int i = 0; i < 5; i++) {
        const int t16 = (lane >> 2) + 8 * i, al = lane & 1, kh = t16 >= 20, tt = t16 - 20 * kh, ii = tt & 3, tau = tt >> 2;
        const int u = tau < 4 ? 2 * ii + al : 8 + al, w4 = tau < 4 ? tau : ii;
        slot[i] = (int)opaque(320 * kh + 16 * (2 * u + (w4 >> 1)) + 8 * (w4 & 1) + (up ? 4 : 0));
    }
    float nmax = 0;
#pragma unroll 1
    for (int n = (int)opaque(LN_WARM ? -1 : 0); n < nrow; n++) {
        if (n == 0) mbar_wait(bar, 0);
        const bool real = n >= 0;
        const int tok = gw + n * LN_WARPS;
        const __nv_bfloat16* xn = g_xn + tok * DM + lane * 4;
        const __half* xnp = g_xnp + tok * DM;
        float f[5][4], sum = 0, sq = 0, r = 0;
#pragma unroll
        for (int i = 0; i < 5; i++) {
            const uint2 v = lds64(rows + (n + 1) * 1280 + lane * 8 + i * 256);
            f[i][0] = bflo(v.x); f[i][1] = bfhi(v.x); f[i][2] = bflo(v.y); f[i][3] = bfhi(v.y);
            sum += (f[i][0] + f[i][1]) + (f[i][2] + f[i][3]);
        }
        const float mean = warp_sum(sum) * (1.0f / DM);
#pragma unroll
        for (int i = 0; i < 5; i++)
#pragma unroll
            for (int e = 0; e < 4; e++) sq = fmaf(f[i][e] - mean, f[i][e] - mean, sq);
        sq = warp_sum(sq);
        float sd, isd;
        asm("sqrt.approx.f32 %0, %1;" : "=f"(sd) : "f"(bf16_round(bf16_round(sq * (1.0f / DM)) + 1e-5f)));
        asm("rcp.approx.f32 %0, %1;" : "=f"(isd) : "f"(bf16_round(sd)));
        const float mb = bf16_round(mean);
        nmax = real ? fmaxf(nmax, fmaf((mean - mb) * (mean - mb), (float)DM, sq) * isd * isd) : 0.0f;
#pragma unroll
        for (int i = 0; i < 5; i++) {
            const uint2 w = lds64(rows + lane * 8 + i * 256);
            const uint32_t d0 = pack_bf16(f[i][0] - mb, f[i][1] - mb), d1 = pack_bf16(f[i][2] - mb, f[i][3] - mb);
            const uint32_t y0 = pack_bf16(bflo(d0) * isd, bfhi(d0) * isd), y1 = pack_bf16(bflo(d1) * isd, bfhi(d1) * isd);
            stg64_if(xn + i * 128, y0, y1, real);
            r = fmaf(bflo(y0), bflo(w.x), fmaf(bfhi(y0), bfhi(w.x), fmaf(bflo(y1), bflo(w.y), fmaf(bfhi(y1), bfhi(w.y), r))));
            const uint32_t o = __shfl_xor_sync(~0u, up ? y0 : y1, 2), lo = up ? o : y0, hi = up ? y1 : o;
            uint32_t h0, h1;
            asm("cvt.rn.satfinite.f16x2.f32 %0, %1, %2;" : "=r"(h0) : "f"(bflo(hi)), "f"(bflo(lo)));
            asm("cvt.rn.satfinite.f16x2.f32 %0, %1, %2;" : "=r"(h1) : "f"(bfhi(hi)), "f"(bfhi(lo)));
            stg64_if(xnp + slot[i], h0, h1, real);
        }
        r = warp_sum(r);
        if (lane == 0 && real) g_r[tok] = bf16_round(r);
        if (n == 0) { __syncwarp(); mbar_arrive_if(sb + MB_L0, lane == 0); }
    }
    __syncwarp();
    if (lane == 0) {
        atomicMax(fl + F_XN, __float_as_uint(sqrtf(nmax) * 1.02f));
        mbar_arrive(sb + MB_L0 + 8);
    }
}

__global__ void __cluster_dims__(3, 1, 1) __launch_bounds__(384, 1)
chain_kernel(const __grid_constant__ Maps maps, const __grid_constant__ Ptrs P) {
    extern __shared__ __align__(1024) unsigned char smem[];
    const bool vs = blockIdx.x % 3 == 2;
    const uint32_t sb = smem_u32(smem);
    const int warp = threadIdx.x >> 5;
    if (threadIdx.x == 32) GT(0);
    if (TRIG == 0) asm volatile("griddepcontrol.launch_dependents;");
    if (threadIdx.x == 0) {
        spin_guard(mapa(sb, 0) == SM_BASE && mapa(sb, 1) == SM_BASE + SM_RANK && mapa(sb, 2) == SM_BASE + 2 * SM_RANK && sb == SM_BASE + blockIdx.x % 3 * SM_RANK ? 0 : ~0u);
        mbar_init(sb + MB_S, 1); mbar_init(sb + MB_V, 1); mbar_init(sb + MB_VX, 1); mbar_init(sb + MB_R, 1); mbar_init(sb + MB_RDY, 2);
        mbar_init(sb + MB_PUB, vs ? 8 : 4); mbar_init(sb + MB_PUB + 8, vs ? 8 : 4);
        mbar_init(sb + MB_XN, 1); mbar_init(sb + MB_XNF, 8); mbar_init(sb + MB_KT, vs ? 8 : 4); mbar_init(sb + MB_KTF, 1);
        mbar_init(sb + MB_AT, 1); mbar_init(sb + MB_AT + 8, 1);
        for (int i = 0; i < 8; i++) mbar_init(sb + MB_KM + i * 8, 1);
        mbar_init(sb + MB_GO, 8); mbar_init(sb + MB_OM, 8); mbar_init(sb + MB_MEM, 8); mbar_init(sb + MB_XN2, 1); mbar_init(sb + MB_CST, 1);
        for (int i = 0; i < 8; i++) mbar_init(sb + MB_PF + i * 8, 1);
        for (int i = 0; i < 3; i++) mbar_init(sb + MB_PE + i * 8, 4);
        for (int i = 0; i < 5; i++) mbar_init(sb + MB_PO + i * 8, 1);
        sts64(sb + SM_CST + 40, 0, 0); sts64(sb + SM_CST + 48, 0, 0); sts64(sb + SM_CST + 56, 0, 0); sts128(sb + SM_AD, 0, 0, 0, 0);
        for (int i = 0; i < 8; i++) mbar_init(sb + MB_LN + i * 8, 1);
        mbar_init(sb + MB_L0, 8); mbar_init(sb + MB_L0 + 8, 8);
        asm volatile("fence.mbarrier_init.release.cluster;" ::: "memory");
    }
    __syncthreads();
    asm volatile("barrier.cluster.arrive.release.aligned; barrier.cluster.wait.acquire.aligned;" ::: "memory");
    if (warp < 8) layernorm_rows(P, sb, blockIdx.x * 8 + warp, threadIdx.x & 31);
    if (TRIG == 1 && warp == 0) asm volatile("griddepcontrol.launch_dependents;");
    if (__builtin_expect(!vs, 1)) {
        if (warp < 8) {
            asm volatile("setmaxnreg.inc.sync.aligned.u32 240;");
            const int cta = cta_now(), h = cta / 3, j = cta - 3 * h;
            chain_main(sb, h, j, warp, tid_now() & 31, P);
            asm volatile("barrier.cluster.arrive.release.aligned; barrier.cluster.wait.acquire.aligned;" ::: "memory");
        } else {
            asm volatile("setmaxnreg.dec.sync.aligned.u32 24;");
            const int cta = cta_now(), h = cta / 3, j = cta - 3 * h;
            chain_aux<false>(sb, 2 * h + j, h, j, warp - 8, tid_now() & 31, &maps, &P);
        }
    } else {
        if (warp < 8) {
            asm volatile("setmaxnreg.inc.sync.aligned.u32 %0;" :: "n"(VS_REGS));
            const int h = cta_now() / 3;
            vs_main(P.sbv, h, warp, tid_now() & 31, P, &maps);
            asm volatile("barrier.cluster.arrive.release.aligned; barrier.cluster.wait.acquire.aligned;" ::: "memory");
        } else {
            asm volatile("setmaxnreg.dec.sync.aligned.u32 %0;" :: "n"(504 - 2 * VS_REGS));
            const int h = cta_now() / 3;
            chain_aux<true>(P.sbv, h, h, 0, warp - 8, tid_now() & 31, &maps, &P);
        }
    }
}

__global__ void __launch_bounds__(384, 1)
gemm_kernel(const __grid_constant__ Maps maps, const __grid_constant__ Ptrs P) {
    extern __shared__ __align__(1024) unsigned char smem[];
    const uint32_t sb = P.sb0;
    const int warp = threadIdx.x >> 5;
    if (threadIdx.x == 0) {
        spin_guard(smem_u32(smem) == SM_BASE ? 0 : ~0u);
        for (int i = 0; i < 4; i++) { mbar_init(sb + GB_QF + i * 8, 1); mbar_init(sb + GB_QE + i * 8, 8); }
        for (int i = 0; i < 8; i++) { mbar_init(sb + GB_OF + i * 8, 1); mbar_init(sb + GB_OE + i * 8, 4); }
        mbar_init(sb + GB_ML, 1); sts64(sb + G_Q, 0, 0); sts64(sb + G_Q + 32, 0, 0);
        mbar_init(sb + GB_WO, 1); mbar_init(sb + GB_QD, 1);
        for (int i = 0; i < 8; i++) mbar_init(sb + MB_LN + i * 8, 1);
        asm volatile("fence.mbarrier_init.release.cluster;" ::: "memory");
    }
    __syncthreads();
    if (threadIdx.x == 0) GT(0);
    if (warp < 8) {
        asm volatile("setmaxnreg.inc.sync.aligned.u32 240;");
        gemm_main(smem, sb, cta_now(), tid_now(), P);
    } else {
        asm volatile("setmaxnreg.dec.sync.aligned.u32 24;");
        const int lane = tid_now() & 31, cta = cta_now();
        if (warp == 11) gemm_publisher(sb, lane);
        else {
            if (warp == 8 && lane == 0) gemm_producer(sb, cta, &maps);
            __syncwarp();
            gemm_producer_o(sb, cta_now(), __reduce_max_sync(~0u, tid_now() >> 5) - 8, tid_now() & 31, P.x);
        }
    }
}

typedef CUresult (*EncodeTiledFn)(CUtensorMap*, CUtensorMapDataType, cuuint32_t, void*, const cuuint64_t*, const cuuint64_t*, const cuuint32_t*,
                                  const cuuint32_t*, CUtensorMapInterleave, CUtensorMapSwizzle, CUtensorMapL2promotion, CUtensorMapFloatOOBfill);
static void make_map(EncodeTiledFn fn, CUtensorMap* m, const void* p, uint64_t cols, uint64_t rows, uint32_t bc, uint32_t br) {
    cuuint64_t dims[2] = {cols, rows}, strides[1] = {cols * 2};
    cuuint32_t box[2] = {bc, br}, es[2] = {1, 1};
    fn(m, CU_TENSOR_MAP_DATA_TYPE_BFLOAT16, 2, const_cast<void*>(p), dims, strides, box, es, CU_TENSOR_MAP_INTERLEAVE_NONE,
       CU_TENSOR_MAP_SWIZZLE_128B, CU_TENSOR_MAP_L2_PROMOTION_L2_256B, CU_TENSOR_MAP_FLOAT_OOB_FILL_NONE);
}

extern "C" void kernel_launch(void* const* d_in, const int* in_sizes, int n_in, void* d_out, int out_size) {
    typedef const __nv_bfloat16* bp;
    void* fp = nullptr; cudaDriverEntryPointQueryResult qr;
    cudaGetDriverEntryPoint("cuTensorMapEncodeTiled", &fp, cudaEnableDefault, &qr);
    EncodeTiledFn enc = (EncodeTiledFn)fp;
    void *xn, *xnp;
    cudaGetSymbolAddress(&xn, g_xn); cudaGetSymbolAddress(&xnp, g_xnp);
    Maps maps;
    make_map(enc, &maps.q, d_in[2], HD, DM, 64, 160); make_map(enc, &maps.k, d_in[3], HD, DM, 64, 160);
    make_map(enc, &maps.v, d_in[4], HD, DM, 64, 160); make_map(enc, &maps.o, d_in[5], DM, HD, 64, 128);
    {
        cuuint64_t dims[3] = {64, S_TOK, 10}, strides[2] = {DM * 2, 128};
        cuuint32_t box[3] = {64, 32, 10}, es[3] = {1, 1, 1};
        enc(&maps.xnp, CU_TENSOR_MAP_DATA_TYPE_BFLOAT16, 3, xnp, dims, strides, box, es, CU_TENSOR_MAP_INTERLEAVE_NONE,
            CU_TENSOR_MAP_SWIZZLE_128B, CU_TENSOR_MAP_L2_PROMOTION_L2_256B, CU_TENSOR_MAP_FLOAT_OOB_FILL_NONE);
    }
    make_map(enc, &maps.xn, xn, DM, S_TOK, 64, 128);
    make_map(enc, &maps.q64, d_in[2], HD, DM, 64, 64); make_map(enc, &maps.o64, d_in[5], DM, HD, 64, 64);
    make_map(enc, &maps.wg, d_in[9], FF, DM, 64, 160); make_map(enc, &maps.wu, d_in[10], FF, DM, 64, 160); make_map(enc, &maps.wd, d_in[11], DM, FF, 64, 64);
    Ptrs P = {(bp)d_in[0], (bp)d_in[1], (bp)d_in[8], (bp)d_in[2], (bp)d_in[3], (bp)d_in[4], (bp)d_in[5], (__nv_bfloat16*)d_out, 0, (uint64_t)WG_DESC_HI << 32 | 1u << 16, (uint64_t)WG_DESC_HI << 32 | (8192u >> 4) << 16, (uint64_t)(1024u >> 4) << 32 | (128u >> 4) << 16, SM_BASE, SM_BASE + 2 * SM_RANK};
    cudaFuncSetAttribute(chain_kernel, cudaFuncAttributeMaxDynamicSharedMemorySize, CHAIN_SMEM);
    cudaFuncSetAttribute(gemm_kernel, cudaFuncAttributeMaxDynamicSharedMemorySize, CHAIN_SMEM);
    chain_kernel<<<96, 384, CHAIN_SMEM>>>(maps, P);
    cudaLaunchConfig_t cfg = {};
    cfg.gridDim = dim3(NG); cfg.blockDim = dim3(384); cfg.dynamicSmemBytes = CHAIN_SMEM; cfg.stream = 0;
    cudaLaunchAttribute at[1];
    at[0].id = cudaLaunchAttributeProgrammaticStreamSerialization; at[0].val.programmaticStreamSerializationAllowed = 1;
    cfg.attrs = at; cfg.numAttrs = 1;
    cudaLaunchKernelEx(&cfg, gemm_kernel, maps, P);
}
```

```cpp
#include <cuda_runtime.h>
#include <cuda_bf16.h>
#include <cuda_fp16.h>
#include <stdint.h>
#include <cuda.h>

constexpr int S_TOK = 2048, DM = 640, NH = 32, DH = 128, NSEG = 64, FF = 1728;
constexpr int HD = NH * DH;

#define TRIG 1
#define LN_CTAS 96
#define POLL_DELAY 1030
#define VS_DELAY POLL_DELAY
#define START_DELAY 0
#define MARK_B 0
#define Q_DEPTH 3
#define O_DEPTH 8
#define O_FAST 28
#define LN_WARM 0
#define W_DEPTH 2
#define VS_REGS 208
#define SU 8
#define PVU 4
#define ATT_GATE 6
#define ATT_EAGER 62
#define ATT_NOW 56
#define ATT_REQ 1
#define ATT_H1 2
#define ATT_H2 4
#define ATT_FLAG 5
#define ATT_STAGE 1
#define ATT_START 0
#define ATT_NAP 60
#define PUB_NAP 40
#define KMDUMP(x)
constexpr int PV_UNROLL = PVU, S_UNROLL = SU;
#define SPIN_LIMIT (1 << 20)

__device__ __align__(1024) __nv_bfloat16 g_xn[S_TOK * DM];
__device__ __align__(1024) __half g_xnp[S_TOK * DM];
constexpr int REC_Q = 0, REC_K = 8192, REC_BYTES = 16384;
__device__ __align__(1024) unsigned char g_kt[NH * 8 * 8192];
__device__ __align__(1024) uint32_t g_ox[S_TOK * HD / 2];
__device__ __align__(1024) uint4 g_part[6 * 7 * 64 * DM / 8];
__device__ __align__(65536) unsigned char g_ring[2 * 32768];
__host__ __device__ constexpr uint32_t ring_pos(uint32_t p) { return (p & 1) * 256 + (p >> 1) * 1024; }
KMDUMP(__device__ unsigned char g_kmd[NH * NSEG * 4096];)
__device__ float g_r[S_TOK];
__device__ __align__(16) float g_y[27 * 8 * DM];
__device__ __align__(16) float g_yf[8 * DM];
__device__ uint32_t g_epoch;
__device__ __align__(1024) uint32_t g_stamp[8 * 256];
__device__ __align__(8) uint32_t g_fkt[NH * 8];
constexpr int F_LN = 0, F_LN0 = 4, F_W = 5, F_INIT = 8, F_MOD = 16, F_YF = 17, F_XN = 24, F_WV = 25, F_WO = 26, F_Q = 32, F_ATT = 48, F_O = 80, F_EPI = 112, F_WORDS = 144;
__device__ __align__(256) uint32_t g_flags[2][F_WORDS];
#define EV(i, x) do {} while (0)
#define TS(role, i, dep) do {} while (0)
#define GT(i) do {} while (0)
#define GTM(i) do {} while (0)
#define AT(i) do {} while (0)
#define VT(s, i) do {} while (0)
#define PROF(i) do {} while (0)

__device__ __forceinline__ int tid_now() { int t; asm volatile("mov.u32 %0, %%tid.x;" : "=r"(t)); return t; }
__device__ __forceinline__ uint32_t clk() { uint64_t c; asm volatile("mov.u64 %0, %%clock64;" : "=l"(c) :: "memory"); return (uint32_t)c; }
__device__ __forceinline__ uint32_t gtime_lo() { uint32_t g; asm volatile("mov.u32 %0, %%globaltimer_lo;" : "=r"(g) :: "memory"); return g; }
__device__ __forceinline__ unsigned long long gtime64() { unsigned long long g; asm volatile("mov.u64 %0, %%globaltimer;" : "=l"(g)); return g; }
__device__ __forceinline__ int cta_now() { int t; asm volatile("mov.u32 %0, %%ctaid.x;" : "=r"(t)); return t; }
__device__ __forceinline__ uint32_t smem_u32(const void* p) { return (uint32_t)__cvta_generic_to_shared(p); }
__device__ __forceinline__ uint32_t mapa(uint32_t a, uint32_t r) { uint32_t o; asm("mapa.shared::cluster.u32 %0, %1, %2;" : "=r"(o) : "r"(a), "r"(r)); return o; }
__device__ __forceinline__ void mma16816(float (&c)[4], uint32_t a0, uint32_t a1, uint32_t a2, uint32_t a3, uint32_t b0, uint32_t b1) {
    asm volatile("mma.sync.aligned.m16n8k16.row.col.f32.bf16.bf16.f32 {%0,%1,%2,%3},{%4,%5,%6,%7},{%8,%9},{%0,%1,%2,%3};"
        : "+f"(c[0]), "+f"(c[1]), "+f"(c[2]), "+f"(c[3]) : "r"(a0), "r"(a1), "r"(a2), "r"(a3), "r"(b0), "r"(b1));
}
__device__ __forceinline__ void mma16816(float (&c)[4], const uint4& a, uint32_t b0, uint32_t b1) { mma16816(c, a.x, a.y, a.z, a.w, b0, b1); }
__device__ __forceinline__ void mma16816h(float (&c)[4], const uint4& a, uint32_t b0, uint32_t b1) {
    asm volatile("mma.sync.aligned.m16n8k16.row.col.f32.f16.f16.f32 {%0,%1,%2,%3},{%4,%5,%6,%7},{%8,%9},{%0,%1,%2,%3};"
        : "+f"(c[0]), "+f"(c[1]), "+f"(c[2]), "+f"(c[3]) : "r"(a.x), "r"(a.y), "r"(a.z), "r"(a.w), "r"(b0), "r"(b1));
}
__device__ __forceinline__ void mma1688(float (&c)[4], uint32_t a0, uint32_t a1, uint32_t b0) {
    asm volatile("mma.sync.aligned.m16n8k8.row.col.f32.bf16.bf16.f32 {%0,%1,%2,%3},{%4,%5},{%6},{%0,%1,%2,%3};"
        : "+f"(c[0]), "+f"(c[1]), "+f"(c[2]), "+f"(c[3]) : "r"(a0), "r"(a1), "r"(b0));
}
__device__ __forceinline__ uint32_t movmat(uint32_t a) { uint32_t d; asm volatile("movmatrix.sync.aligned.m8n8.trans.b16 %0, %1;" : "=r"(d) : "r"(a)); return d; }
__device__ __forceinline__ uint32_t pack_bf16(float lo, float hi) { uint32_t d; asm("cvt.rn.bf16x2.f32 %0, %1, %2;" : "=r"(d) : "f"(hi), "f"(lo)); return d; }
__device__ __forceinline__ uint32_t pack_f16(float lo, float hi) { uint32_t d; asm("cvt.rn.f16x2.f32 %0, %1, %2;" : "=r"(d) : "f"(hi), "f"(lo)); return d; }
__device__ __forceinline__ uint32_t bf16x2_to_f16x2(uint32_t w, float sc) {
    const uint32_t s2 = (__float_as_uint(sc) >> 16) | __float_as_uint(sc);
    asm("mul.rn.bf16x2 %0, %0, %1;" : "+r"(w) : "r"(s2));
    return pack_f16(__uint_as_float(w << 16), __uint_as_float(w & 0xffff0000u));
}
__device__ __forceinline__ uint32_t bf16x2_to_f16x2p(uint32_t w, uint32_t s2) {
    asm("mul.rn.bf16x2 %0, %0, %1;" : "+r"(w) : "r"(s2));
    return pack_f16(__uint_as_float(w << 16), __uint_as_float(w & 0xffff0000u));
}
__device__ __forceinline__ int f16_exp(float bound) { return min(max(141 - (int)((__float_as_uint(bound) >> 23) & 255u), -110), 110); }
__device__ __forceinline__ float pow2i(int k) { return __uint_as_float((uint32_t)(127 + k) << 23); }
__device__ __forceinline__ float ex2(float x) { float y; asm("ex2.approx.ftz.f32 %0, %1;" : "=f"(y) : "f"(x)); return y; }
__device__ __forceinline__ uint4 lds128(uint32_t a) { uint4 v; asm volatile("ld.volatile.shared.v4.u32 {%0,%1,%2,%3}, [%4];" : "=r"(v.x), "=r"(v.y), "=r"(v.z), "=r"(v.w) : "r"(a) : "memory"); return v; }
__device__ __forceinline__ uint32_t lds32(uint32_t a) { uint32_t v; asm volatile("ld.volatile.shared.u32 %0, [%1];" : "=r"(v) : "r"(a) : "memory"); return v; }
__device__ __forceinline__ uint2 lds64(uint32_t a) { uint2 v; asm volatile("ld.volatile.shared.v2.u32 {%0,%1}, [%2];" : "=r"(v.x), "=r"(v.y) : "r"(a) : "memory"); return v; }
__device__ __forceinline__ void sts128(uint32_t a, uint32_t x, uint32_t y, uint32_t z, uint32_t w) { asm volatile("st.volatile.shared.v4.u32 [%0], {%1,%2,%3,%4};" :: "r"(a), "r"(x), "r"(y), "r"(z), "r"(w) : "memory"); }
__device__ __forceinline__ void sts128(uint32_t a, const uint4& v) { sts128(a, v.x, v.y, v.z, v.w); }
__device__ __forceinline__ void sts128f(uint32_t a, float x, float y, float z, float w) { sts128(a, __float_as_uint(x), __float_as_uint(y), __float_as_uint(z), __float_as_uint(w)); }
__device__ __forceinline__ void sts64(uint32_t a, uint32_t x, uint32_t y) { asm volatile("st.volatile.shared.v2.u32 [%0], {%1,%2};" :: "r"(a), "r"(x), "r"(y) : "memory"); }
__device__ __forceinline__ void sts32(uint32_t a, uint32_t x) { asm volatile("st.volatile.shared.u32 [%0], %1;" :: "r"(a), "r"(x) : "memory"); }
__device__ __forceinline__ uint4 ldsm4(uint32_t a) { uint4 v; asm volatile("ldmatrix.sync.aligned.m8n8.x4.shared.b16 {%0,%1,%2,%3}, [%4];" : "=r"(v.x), "=r"(v.y), "=r"(v.z), "=r"(v.w) : "r"(a) : "memory"); return v; }
__device__ __forceinline__ uint4 ldsm4t(uint32_t a) { uint4 v; asm volatile("ldmatrix.sync.aligned.m8n8.x4.trans.shared.b16 {%0,%1,%2,%3}, [%4];" : "=r"(v.x), "=r"(v.y), "=r"(v.z), "=r"(v.w) : "r"(a) : "memory"); return v; }
__device__ __forceinline__ uint4 ldsm4t_if(uint32_t a, uint32_t c) { uint4 v; asm volatile("{.reg .pred p; setp.ne.u32 p, %5, 0; @p ldmatrix.sync.aligned.m8n8.x4.trans.shared.b16 {%0,%1,%2,%3}, [%4];}" : "=r"(v.x), "=r"(v.y), "=r"(v.z), "=r"(v.w) : "r"(a), "r"(c) : "memory"); return v; }
__device__ __forceinline__ uint4 lds128_if(uint32_t a, uint32_t c) { uint4 v; asm volatile("{.reg .pred p; setp.ne.u32 p, %5, 0; @p ld.volatile.shared.v4.u32 {%0,%1,%2,%3}, [%4];}" : "=r"(v.x), "=r"(v.y), "=r"(v.z), "=r"(v.w) : "r"(a), "r"(c) : "memory"); return v; }
__device__ __forceinline__ void stsm4(uint32_t a, uint32_t x, uint32_t y, uint32_t z, uint32_t w) { asm volatile("stmatrix.sync.aligned.m8n8.x4.shared.b16 [%0], {%1,%2,%3,%4};" :: "r"(a), "r"(x), "r"(y), "r"(z), "r"(w) : "memory"); }
__device__ __forceinline__ void stsm4t(uint32_t a, uint32_t x, uint32_t y, uint32_t z, uint32_t w) { asm volatile("stmatrix.sync.aligned.m8n8.x4.trans.shared.b16 [%0], {%1,%2,%3,%4};" :: "r"(a), "r"(x), "r"(y), "r"(z), "r"(w) : "memory"); }
__device__ __forceinline__ void bar_sync(int id, int n) { asm volatile("bar.sync %0, %1;" :: "r"(id), "r"(n) : "memory"); }
__device__ __forceinline__ void bar_sync_if(int id, int n, bool c) { asm volatile("{.reg .pred p; setp.ne.u32 p, %2, 0; @p bar.sync %0, %1;}" :: "r"(id), "r"(n), "r"((uint32_t)c) : "memory"); }
__device__ __forceinline__ void mbar_init(uint32_t a, uint32_t c) { asm volatile("mbarrier.init.shared::cta.b64 [%0], %1;" :: "r"(a), "r"(c) : "memory"); }
__device__ __forceinline__ void mbar_arrive(uint32_t a) { asm volatile("mbarrier.arrive.shared::cta.b64 _, [%0];" :: "r"(a) : "memory"); }
__device__ __forceinline__ void mbar_arrive_tx(uint32_t a, uint32_t tx) { asm volatile("mbarrier.arrive.expect_tx.shared::cta.b64 _, [%0], %1;" :: "r"(a), "r"(tx) : "memory"); }
__device__ __forceinline__ void spin_guard(uint32_t n) { asm volatile("{.reg .pred p; setp.gt.u32 p, %0, %1; @p st.shared.u32 [%0], %0;}" :: "r"(n), "n"(SPIN_LIMIT) : "memory"); }
__device__ __forceinline__ void mbar_wait(uint32_t a, uint32_t ph) {
    asm volatile("{\n.reg .pred p, q;\n.reg .u32 n;\nmov.u32 n, 0;\n"
                 "MW_LOOP:\nmbarrier.try_wait.parity.shared::cta.b64 p, [%0], %1;\n"
                 "add.u32 n, n, 1;\nsetp.gt.u32 q, n, %2;\n@q st.shared.u32 [n], n;\n@!p bra.uni MW_LOOP;\n}"
                 :: "r"(a), "r"(ph), "n"(SPIN_LIMIT) : "memory");
}
__device__ __forceinline__ uint32_t mbar_try(uint32_t a, uint32_t ph) {
    uint32_t ok;
    asm volatile("{.reg .pred p; mbarrier.test_wait.parity.shared::cta.b64 p, [%1], %2; selp.u32 %0, 1, 0, p;}" : "=r"(ok) : "r"(a), "r"(ph) : "memory");
    return ok;
}
__device__ __forceinline__ uint32_t mbar_try_wait(uint32_t a, uint32_t ph) {
    uint32_t ok;
    asm volatile("{.reg .pred p; mbarrier.try_wait.parity.shared::cta.b64 p, [%1], %2; selp.u32 %0, 1, 0, p;}" : "=r"(ok) : "r"(a), "r"(ph) : "memory");
    return ok;
}
__device__ __forceinline__ void wait_clk(uint32_t c0, uint32_t d) {
    asm volatile("{\n.reg .pred p;\n.reg .u32 c;\n.reg .u64 x;\nWC_LOOP:\nmov.u64 x, %%clock64;\ncvt.u32.u64 c, x;\nsub.u32 c, c, %0;\nsetp.lt.s32 p, c, %1;\n@p bra.uni WC_LOOP;\n}" :: "r"(c0), "r"(d) : "memory");
}
__device__ __forceinline__ void sts32_if(uint32_t a, uint32_t x, bool c) { asm volatile("{.reg .pred p; setp.ne.u32 p, %2, 0; @p st.volatile.shared.u32 [%0], %1;}" :: "r"(a), "r"(x), "r"((uint32_t)c) : "memory"); }
__device__ __forceinline__ float rcp(float x) { float y; asm("rcp.approx.ftz.f32 %0, %1;" : "=f"(y) : "f"(x)); return y; }
__device__ __forceinline__ float uf(uint32_t x) { return __uint_as_float(x); }
__device__ __forceinline__ void mbar_arrive_remote_if(uint32_t a, bool c) { asm volatile("{.reg .pred p; setp.ne.u32 p, %1, 0; @p mbarrier.arrive.relaxed.cluster.shared::cluster.b64 _, [%0];}" :: "r"(a), "r"((uint32_t)c) : "memory"); }
__device__ __forceinline__ void mbar_arrive_if(uint32_t a, bool c) { asm volatile("{.reg .pred p; setp.ne.u32 p, %1, 0; @p mbarrier.arrive.shared::cta.b64 _, [%0];}" :: "r"(a), "r"((uint32_t)c) : "memory"); }
__device__ __forceinline__ void mbar_arrive_tx_if(uint32_t a, uint32_t tx, bool c) { asm volatile("{.reg .pred p; setp.ne.u32 p, %2, 0; @p mbarrier.arrive.expect_tx.shared::cta.b64 _, [%0], %1;}" :: "r"(a), "r"(tx), "r"((uint32_t)c) : "memory"); }
__device__ __forceinline__ void tma2d(uint32_t dst, const CUtensorMap* m, int c0, int c1, uint32_t mb) {
    asm volatile("cp.async.bulk.tensor.2d.shared::cluster.global.mbarrier::complete_tx::bytes [%0], [%1, {%2, %3}], [%4];" :: "r"(dst), "l"(m), "r"(c0), "r"(c1), "r"(mb) : "memory");
}
__device__ __forceinline__ void tma3d(uint32_t dst, const CUtensorMap* m, int c0, int c1, int c2, uint32_t mb) {
    asm volatile("cp.async.bulk.tensor.3d.shared::cluster.global.mbarrier::complete_tx::bytes [%0], [%1, {%2, %3, %4}], [%5];" :: "r"(dst), "l"(m), "r"(c0), "r"(c1), "r"(c2), "r"(mb) : "memory");
}
__device__ __forceinline__ void tma_xn(uint32_t dst, const CUtensorMap* m, int g, uint32_t mb) {
    asm volatile("{.reg .pred p; elect.sync _|p, 0xffffffff;\n@p mbarrier.arrive.expect_tx.shared::cta.b64 _, [%2], 40960;\n"
                 "@p cp.async.bulk.tensor.3d.shared::cluster.global.mbarrier::complete_tx::bytes [%0], [%1, {0, %3, 0}], [%2];}" :: "r"(dst), "l"(m), "r"(mb), "r"(32 * g) : "memory");
}
__device__ __forceinline__ void tma2d_prefetch(const CUtensorMap* m, int c0, int c1) {
    asm volatile("cp.async.bulk.prefetch.tensor.2d.L2.global [%0, {%1, %2}];" :: "l"(m), "r"(c0), "r"(c1) : "memory");
}
__device__ __forceinline__ void st_async128_if(uint32_t a, float x, float y, float z, float w, uint32_t mb, bool c) {
    asm volatile("{.reg .pred p; setp.ne.u32 p, %6, 0; @p st.async.shared::cluster.mbarrier::complete_tx::bytes.v4.f32 [%0], {%1,%2,%3,%4}, [%5];}" :: "r"(a), "f"(x), "f"(y), "f"(z), "f"(w), "r"(mb), "r"((uint32_t)c) : "memory");
}
__device__ __forceinline__ void st_async128(uint32_t a, float x, float y, float z, float w, uint32_t mb) {
    asm volatile("st.async.shared::cluster.mbarrier::complete_tx::bytes.v4.f32 [%0], {%1,%2,%3,%4}, [%5];" :: "r"(a), "f"(x), "f"(y), "f"(z), "f"(w), "r"(mb) : "memory");
}
__device__ __forceinline__ void st_async32(uint32_t a, uint32_t x, uint32_t mb) {
    asm volatile("st.async.shared::cluster.mbarrier::complete_tx::bytes.b32 [%0], %1, [%2];" :: "r"(a), "r"(x), "r"(mb) : "memory");
}
__device__ __forceinline__ void st_async64(uint32_t a, uint32_t x, uint32_t y, uint32_t mb) {
    asm volatile("st.async.shared::cluster.mbarrier::complete_tx::bytes.v2.b32 [%0], {%1,%2}, [%3];" :: "r"(a), "r"(x), "r"(y), "r"(mb) : "memory");
}
__device__ __forceinline__ void st_async64_if(uint32_t a, uint32_t x, uint32_t y, uint32_t mb, bool c) {
    asm volatile("{.reg .pred p; setp.ne.u32 p, %4, 0; @p st.async.shared::cluster.mbarrier::complete_tx::bytes.v2.b32 [%0], {%1,%2}, [%3];}" :: "r"(a), "r"(x), "r"(y), "r"(mb), "r"((uint32_t)c) : "memory");
}
__device__ __forceinline__ void bulk_g2s(uint32_t dst, const void* src, uint32_t bytes, uint32_t mb) {
    asm volatile("cp.async.bulk.shared::cluster.global.mbarrier::complete_tx::bytes [%0], [%1], %2, [%3];" :: "r"(dst), "l"(src), "r"(bytes), "r"(mb) : "memory");
}
__device__ __forceinline__ void bulk_g2s_mc(uint32_t dst, const void* src, uint32_t bytes, uint32_t mb, uint16_t mask) {
    asm volatile("cp.async.bulk.shared::cluster.global.mbarrier::complete_tx::bytes.multicast::cluster [%0], [%1], %2, [%3], %4;" :: "r"(dst), "l"(src), "r"(bytes), "r"(mb), "h"(mask) : "memory");
}
__device__ __forceinline__ void bulk_s2s(uint32_t dst, uint32_t src, uint32_t bytes, uint32_t mb) {
    asm volatile("cp.async.bulk.shared::cluster.shared::cta.mbarrier::complete_tx::bytes [%0], [%1], %2, [%3];" :: "r"(dst), "r"(src), "r"(bytes), "r"(mb) : "memory");
}
__device__ __forceinline__ void bulk_s2g(void* dst, uint32_t src, uint32_t bytes) {
    asm volatile("cp.async.bulk.global.shared::cta.bulk_group [%0], [%1], %2;\ncp.async.bulk.commit_group;" :: "l"(dst), "r"(src), "r"(bytes) : "memory");
}
__device__ __forceinline__ void bulk_prefetch(const void* p, uint32_t bytes) { asm volatile("cp.async.bulk.prefetch.L2.global [%0], %1;" :: "l"(p), "r"(bytes) : "memory"); }
__device__ __forceinline__ void bulk_wait_all() { asm volatile("cp.async.bulk.wait_group 0;" ::: "memory"); }
__device__ __forceinline__ void fence_release() { asm volatile("fence.release.gpu;" ::: "memory"); }
__device__ __forceinline__ void fence_async() { asm volatile("fence.proxy.async.global;" ::: "memory"); }
__device__ __forceinline__ void fence_async_smem() { asm volatile("fence.proxy.async.shared::cta;" ::: "memory"); }
__device__ __forceinline__ void bar_arrive(int id, int n) { asm volatile("bar.arrive %0, %1;" :: "r"(id), "r"(n) : "memory"); }
__device__ __forceinline__ uint32_t ld_acquire(const uint32_t* p) { uint32_t v; asm volatile("ld.acquire.gpu.global.u32 %0, [%1];" : "=r"(v) : "l"(p) : "memory"); return v; }
__device__ __forceinline__ void wait_flag(const uint32_t* p, uint32_t target) { uint32_t n = 0; while ((int)(ld_acquire(p) - target) < 0) { spin_guard(++n); __nanosleep(64); } }
__device__ __forceinline__ void wg_fence() { asm volatile("wgmma.fence.sync.aligned;" ::: "memory"); }
__device__ __forceinline__ void wg_commit() { asm volatile("wgmma.commit_group.sync.aligned;" ::: "memory"); }
template <int N> __device__ __forceinline__ void wg_wait() { asm volatile("wgmma.wait_group.sync.aligned %0;" :: "n"(N) : "memory"); }
__device__ __forceinline__ uint32_t wg_desc_lo(uint32_t addr, uint32_t lbo) { return ((addr & 0x3FFFF) >> 4) | ((lbo >> 4) << 16); }
constexpr uint32_t WG_DESC_HI = (1024u >> 4) | (1u << 30);
template <int ACC>
__device__ __forceinline__ void wgmma_n32_rs(float (&c)[16], const uint4& a, uint64_t d) {
    asm volatile("wgmma.mma_async.sync.aligned.m64n32k16.f32.f16.f16 {%0,%1,%2,%3,%4,%5,%6,%7,%8,%9,%10,%11,%12,%13,%14,%15},{%16,%17,%18,%19},%20,%21,1,1,0;"
        : "+f"(c[0]), "+f"(c[1]), "+f"(c[2]), "+f"(c[3]), "+f"(c[4]), "+f"(c[5]), "+f"(c[6]), "+f"(c[7]),
          "+f"(c[8]), "+f"(c[9]), "+f"(c[10]), "+f"(c[11]), "+f"(c[12]), "+f"(c[13]), "+f"(c[14]), "+f"(c[15])
        : "r"(a.x), "r"(a.y), "r"(a.z), "r"(a.w), "l"(d), "n"(ACC));
}
__device__ __forceinline__ uint4 ld_relaxed128(const void* p) { uint4 v; asm volatile("ld.relaxed.gpu.global.v4.u32 {%0,%1,%2,%3}, [%4];" : "=r"(v.x), "=r"(v.y), "=r"(v.z), "=r"(v.w) : "l"(p) : "memory"); return v; }
__device__ __forceinline__ uint2 ld_relaxed64(const void* p) { uint2 v; asm volatile("ld.relaxed.gpu.global.v2.u32 {%0,%1}, [%2];" : "=r"(v.x), "=r"(v.y) : "l"(p) : "memory"); return v; }
__device__ __forceinline__ void ld_relaxed128_if(uint4& v, const void* p, uint32_t c) { asm volatile("{.reg .pred p; setp.ne.u32 p, %5, 0; @p ld.relaxed.gpu.global.v4.u32 {%0,%1,%2,%3}, [%4];}" : "+r"(v.x), "+r"(v.y), "+r"(v.z), "+r"(v.w) : "l"(p), "r"(c) : "memory"); }
__device__ __forceinline__ void ld_relaxed64_if(uint4& v, const void* p, uint32_t c) { asm volatile("{.reg .pred p; setp.ne.u32 p, %3, 0; @p ld.relaxed.gpu.global.v2.u32 {%0,%1}, [%2];}" : "+r"(v.x), "+r"(v.y) : "l"(p), "r"(c) : "memory"); }
__device__ __forceinline__ void st_relaxed128(void* p, uint4 v) { asm volatile("st.relaxed.gpu.global.v4.u32 [%0], {%1,%2,%3,%4};" :: "l"(p), "r"(v.x), "r"(v.y), "r"(v.z), "r"(v.w) : "memory"); }
__device__ __forceinline__ uint32_t ld_relaxed32(const void* p) { uint32_t v; asm volatile("ld.relaxed.gpu.global.u32 %0, [%1];" : "=r"(v) : "l"(p) : "memory"); return v; }
__device__ __forceinline__ void st_relaxed32(void* p, uint32_t v) { asm volatile("st.relaxed.gpu.global.u32 [%0], %1;" :: "l"(p), "r"(v) : "memory"); }
__device__ __forceinline__ void red_h8(void* p, uint32_t a, uint32_t b, uint32_t c, uint32_t d) {
    asm volatile("red.relaxed.gpu.global.add.noftz.v4.f16x2 [%0], {%1,%2,%3,%4};" :: "l"(p), "r"(a), "r"(b), "r"(c), "r"(d) : "memory");
}
__device__ __forceinline__ void red_h4(void* p, uint32_t a, uint32_t b) {
    asm volatile("red.relaxed.gpu.global.add.noftz.v2.f16x2 [%0], {%1,%2};" :: "l"(p), "r"(a), "r"(b) : "memory");
}
__device__ __forceinline__ void red_add_if(uint32_t* p, uint32_t v, bool c) { asm volatile("{.reg .pred p; setp.ne.u32 p, %2, 0; @p red.relaxed.gpu.global.add.u32 [%0], %1;}" :: "l"(p), "r"(v), "r"((uint32_t)c) : "memory"); }
__device__ __forceinline__ uint32_t ldg32(const void* p) { uint32_t v; asm volatile("ld.global.nc.L1::no_allocate.u32 %0, [%1];" : "=r"(v) : "l"(p)); return v; }
__device__ __forceinline__ unsigned char* kt_ptr(int h, int s) { return g_kt + (uint32_t)((h * 8 + (s & 7)) * 8192); }
__device__ __forceinline__ uint32_t* ox_ptr(int h, int s) { return g_ox + (uint32_t)(((s >> 1) * 64 + 2 * h) * 2048 + (s & 1) * 1024); }
__device__ __forceinline__ float bf16_round(float x) { return __uint_as_float(pack_bf16(0.0f, x)); }

#define A_RES 7
#define B_RES 8
#define A_DISP 4
#define B_DISP 5
#define A_P1 0
#define A_P2 4
#define A_P3 5
#define B_P1 2
#define B_P2 8
#define A_RL 0
#define B_RL 2
#define A_DEPTH 3
#define B_DEPTH 4
#define VXN_AT 7
#define PH_AT 0
#define CARRY 2
#define VX_PRE 4
#define AM_AT 0
#define SPEC_ST 1
#define V_SPLIT 10
#define POLL_EARLY 850
#define A_SPLIT 20
#define B_SPLIT 12
#define LATE_AT 6
#define NO_MAX 20
#define V_ST_FIRST 0
#define SIG_DEAD 100
#define SIG_V 0
#define SIG_POLL 400
#define A_RL2 2
#define P1_ILP 2
#define PH_W 4
#define ROLE_SWAP 1
#define V_FIRST 0
#define PUB_RED 0
#define K_AHEAD 2
#define K_NAP 40
#define P_NAP 0
#define PQ_AT 8
#define SWAP_AB 0
#define EARLY_P 8
#define POLL_MEM 0
#define PRE_ILP 2
#define XN_AT 1
#define XN_NAP 0
#define A_ILP 2
#define B_ACC2 0
#define POLL_MAX 4000
#define PUB_LATE 1
#define V_TAIL 0
#define V_LEAD 0
#define V_DEPTH 4
#define TP_SPLIT 12
#define OB_DEP 0
#define B_GO -1
#define A_P0 0
#define V_PACE 1
#define P_PACE 0
#define KX_AT 5
#define G_WAIT 0
#define V_SEND 1
#define G_NAP 40
#define E_NAP 300
#define B_ADV 0
#define V_SEP 0
#define B_HOLD 0
#define PF_MODE 0
#define PF_NAP 0
#define W_DEPTH_V 3
#define G_PACE 200
#define PF_FROM 40
#define V_ORDER 1
#define XN_EARLY 0
#define V_POLL 0
#define WG_DELAY 0
#define VW_DELAY 0
#define RL_PRE 0
#define MB_DEPTH 3
constexpr int X_RES = 5, A_SW = 24 - X_RES, B_SW = 16 - X_RES, T_SW = A_SW + B_SW, T_DISP = A_DISP + B_DISP;
constexpr int SM_BASE = 1024;
constexpr uint32_t SM_RANK = 1u << 24;
constexpr int SM_FO = 0;
constexpr int SM_XP = 61440;
constexpr int SM_KT0 = SM_XP + 4096;
constexpr int SM_MEM = SM_KT0 + 4096, MV = 608;
constexpr int SM_KT1 = 81920;
constexpr int SM_XQ = SM_KT1 + 4096;
constexpr int SM_QM = SM_XQ + 4096, SM_KMM = SM_QM + 1024;
constexpr int SM_ONE = SM_KMM + 256, SM_USC = SM_KMM + 768;
constexpr int SM_SLOC = SM_KMM + 2048;
constexpr int SM_OB = SM_SLOC + 1536;
constexpr int SM_LS = SM_OB + 2048;
constexpr int SM_AM = SM_LS + 1024;
constexpr int SM_SREM = SM_AM + 1024;
constexpr int SM_VM = SM_SREM + 1536;
constexpr int SM_FQ = SM_VM + 2048;
constexpr int SM_VX = 167936, SM_VX2 = SM_VX + 8192;
constexpr int SM_XN = 184320;
static_assert(T_SW <= 30 && SM_MEM + 20 * MV <= SM_KT1 && SM_FQ + T_DISP * 2048 <= SM_VX, "smem layout");
constexpr int SM_CST = 229376;
constexpr int SM_BAR = SM_CST + 64;
constexpr int MB_S = SM_BAR, MB_V = SM_BAR + 8, MB_VX = SM_BAR + 16, MB_VF = SM_BAR + 16  , MB_PUB = SM_BAR + 32  ,
              MB_XN = SM_BAR + 56, MB_XNF = SM_BAR + 64, MB_KT = SM_BAR + 72, MB_KTF = SM_BAR + 80,
              MB_PF = SM_BAR + 104  , MB_PE = SM_BAR + 168  , MB_GO = SM_BAR + 192, MB_PO = SM_BAR + 256  ,
              MB_ST = SM_BAR  , MB_R = SM_BAR + 96, MB_RDY = SM_BAR + 48, MB_OM = SM_BAR + 88, MB_MEM = SM_BAR + 200, MB_XN2 = SM_BAR + 208, MB_CST = SM_BAR + 216;
static_assert(MB_V == MB_S + 8 && MB_VX == MB_S + 16, "barriers");
constexpr int SM_XN2 = 0;
constexpr int SM_AT = 81920, MB_AT = SM_BAR + 224  ;
constexpr int NVR = 6, SM_VR = SM_AT + 2 * REC_BYTES;
constexpr int NKM = 8, SM_KM = 40960, MB_KM = SM_BAR + 320  ;
constexpr int SM_MEMV = SM_VR + NVR * 8192;
constexpr int SM_AO0 = SM_KM + NKM * 4096, SM_AO1 = SM_XN - 8192;
static_assert(SM_AO0 + 8192 <= SM_AT && SM_MEMV + 20 * MV <= SM_AO1, "smem layout");
static_assert(SM_MEMV >= 163840 && SM_MEMV + 20 * MV <= SM_XN && SM_KM + NKM * 4096 <= SM_AT, "smem layout");
constexpr int SM_PROF = SM_BAR + 320;
constexpr int MB_L0 = SM_PROF + 112  , MB_LN = SM_PROF + 128  , LN_WARPS = LN_CTAS * 8;
constexpr int SM_RV = SM_PROF + 192, SM_IK = SM_PROF + 208;
constexpr int CHAIN_SMEM = SM_PROF + 1024;
static_assert(CHAIN_SMEM <= 232448, "smem");
constexpr int STG_O = 0, STG_QK = 81920, STG_V = 0;

constexpr int BAR_MEMA = 1, BAR_MEMB = 2, BAR_PAIR = 3  , BAR_RED = 7, BAR_O = 8, BAR_ALL = 9, BAR_C = 10, BAR_BGO = 11, BAR_PW = 12, BAR_LATE = 13, BAR_MEM = 14  ;
#define QK_PRE 3
#define B_W1 11
#define B_W2 B_SW
#define A_PRE2 8
#define POLL_DELAY_A 150
constexpr uint32_t CNT_ONE = 0x3c003c00u, CNT_FULL = 0x50005000u, BF_ONES = 0x3f803f80u;

struct Maps { CUtensorMap q, k, v, o, xnp, xn, q64, o64, wg, wu, wd; };
struct Ptrs { const __nv_bfloat16 *x, *mem0, *wr, *wq, *wk, *wv, *wo; __nv_bfloat16* out; uint32_t zero; uint64_t desc, desc_b, desc_oa; uint32_t sb0, sbv; };

__device__ __forceinline__ uint32_t launch_tag() { return *(volatile uint32_t*)&g_epoch * NSEG + 1; }
__device__ __forceinline__ uint32_t* launch_flags() { return g_flags[*(volatile uint32_t*)&g_epoch & 1]; }
__device__ __forceinline__ void flag_add(uint32_t* p) { asm volatile("red.release.gpu.global.add.u32 [%0], 1;" :: "l"(p) : "memory"); }
__device__ __forceinline__ void wait_count(uint32_t a, uint32_t v) {
    uint32_t n = 0, x;
    while (true) {
        asm volatile("ld.acquire.cta.shared.u32 %0, [%1];" : "=r"(x) : "r"(a) : "memory");
        if (__all_sync(~0u, x >= v)) break;
        spin_guard(++n >> 2);
    }
}
constexpr int SM_PH = SM_CST + 60;
constexpr int SM_RC = SM_BAR + 240;
constexpr int SM_AD = SM_BAR + 304;
__device__ __forceinline__ void wait_att(uint32_t sb, int g) {
    uint32_t n = 0;
    while (lds32(sb + SM_AD + (g & 1) * 4) <= (uint32_t)(g >> 1)) spin_guard(++n >> 4);
}
__device__ __forceinline__ uint32_t opaque(uint32_t x) { asm volatile("" : "+r"(x)); return x; }
__device__ __forceinline__ uint32_t pin(uint32_t x) { return __shfl_sync(~0u, x, threadIdx.x & 31); }
__device__ __forceinline__ void sfence(uint32_t z) { asm volatile("{.reg .pred p; setp.ne.u32 p, %0, 0; @p griddepcontrol.launch_dependents;}" :: "r"(z) : "memory"); }
__device__ __forceinline__ float lg2(float x) { float y; asm("lg2.approx.ftz.f32 %0, %1;" : "=f"(y) : "f"(x)); return y; }
__device__ __forceinline__ uint2 ldsm2t(uint32_t a) { uint2 v; asm volatile("ldmatrix.sync.aligned.m8n8.x2.trans.shared.b16 {%0,%1}, [%2];" : "=r"(v.x), "=r"(v.y) : "r"(a) : "memory"); return v; }
__device__ __forceinline__ uint32_t exp_or_mark(float z) {
    uint32_t e;
    asm volatile("{.reg .pred p; .reg .f32 a; .reg .b32 m; ex2.approx.ftz.f32 %0, %1; abs.f32 a, %1; setp.gtu.f32 p, a, 0f42200000; shf.r.wrap.b32 m, %1, 1, 1; selp.b32 %0, m, %0, p;}" : "=&r"(e) : "r"(__float_as_uint(z)));
    return e;
}
__device__ __forceinline__ uint32_t after(uint32_t a, uint32_t x, uint32_t z) { return a | (x & z); }

__device__ __forceinline__ uint32_t absmax2(uint32_t a, uint32_t b) { uint32_t d; asm("max.xorsign.abs.bf16x2 %0, %1, %2;" : "=r"(d) : "r"(a), "r"(b)); return d; }
__device__ __forceinline__ uint32_t absmax8(uint32_t a, const uint4& x) { return absmax2(absmax2(a, absmax2(x.x, x.y)), absmax2(x.z, x.w)); }
__device__ __forceinline__ uint32_t warp_absmax(uint32_t a) { return __reduce_max_sync(~0u, max((a & 0x7fffu) << 16, a & 0x7fff0000u)); }
__device__ __forceinline__ uint32_t tile_off(int ch0, int lane, int al) {
    const int sg = lane & 7, row = 4 * al + (sg >> 1) + 8 * (sg & 1);
    return row * 128 + (((ch0 + ((lane >> 3) & 1)) ^ (row & 7)) << 4);
}
template <class F>
__device__ __forceinline__ uint32_t load_tile(uint4 (&w)[20], int& ke, uint32_t slot0, uint32_t dslot, int ch0, int lane, uint32_t zr, F released) {
    const uint32_t o0 = slot0 + tile_off(ch0, lane, 0), o1 = slot0 + tile_off(ch0, lane, 1), mh = lane >> 4, dj = dslot - 20480;
    uint32_t a = 0;
#pragma unroll
    for (int k = 0; k < 20; k++) {
        const uint32_t o = ((k >> 1) & 1) ? o1 : o0;
        const int n = k < 16 ? 8 * (k & 1) + (k >> 2) : 16 + 2 * (k & 1);
        w[k] = ldsm4t(o + n * 2048 + (k >= 16 ? dj + mh * 2048 : n >= 10 ? dj + mh * 8192 : n >= 8 ? mh * (dj + 8192) : mh * 8192));
    }
#pragma unroll
    for (int k = 0; k < 20; k++) a = absmax8(a, w[k]);
    a = warp_absmax(a);
    released(a);
    ke = f16_exp(uf(a));
    uint32_t s2 = (uint32_t)(127 + ke) * 0x00800080u;
#pragma unroll
    for (int k = 0; k < 20; k++) {
        w[k].x = bf16x2_to_f16x2p(w[k].x, s2); w[k].y = bf16x2_to_f16x2p(w[k].y, s2); w[k].z = bf16x2_to_f16x2p(w[k].z, s2); w[k].w = bf16x2_to_f16x2p(w[k].w, s2);
        if (k & 1) s2 = after(s2, w[k].x, zr);
    }
    return a;
}
__device__ __forceinline__ uint32_t all_of(const uint4 (&w)[20]) {
    uint32_t a = 0;
#pragma unroll
    for (int k = 0; k < 20; k++) a |= w[k].w;
    return a;
}

template <bool FIRST = true, bool LAST = true, int K0 = 0, int K1 = 20>
__device__ __forceinline__ void tp_issue(float (&c)[16], const uint4 (&w)[20], uint32_t xn, uint64_t dbase) {
    const uint64_t d0 = dbase + ((SM_BASE + xn) >> 4);
    if (FIRST || K0) wg_fence();
#pragma unroll
    for (int k = K0; k < K1; k++) {
        const uint64_t d = d0 + (((k >> 2) * 4096 + (k & 3) * 32) >> 4);
        if (k == 0 && FIRST) wgmma_n32_rs<0>(c, w[k], d); else wgmma_n32_rs<1>(c, w[k], d);
    }
    if (LAST) wg_commit();
}
__device__ __forceinline__ void tp_dump_k(uint32_t xp, float (&c)[16]) {
    constexpr float f = 1.0f / 512;
#pragma unroll
    for (int n = 0; n < 2; n++) sts128(xp + n * 2048, pack_f16(c[8 * n] * f, c[8 * n + 1] * f), pack_f16(c[8 * n + 2] * f, c[8 * n + 3] * f), pack_f16(c[8 * n + 4] * f, c[8 * n + 5] * f), pack_f16(c[8 * n + 6] * f, c[8 * n + 7] * f));
}
__device__ __forceinline__ uint32_t kt_lane(uint32_t sb, int t, int lane) { return sb + (t >> 1) * 2048 + (t & 1) * 256 + (lane >> 4) * 512 + (lane & 15) * 16; }
__device__ __forceinline__ void tp_combine_k(uint32_t sb, uint32_t xp, uint32_t dst, const float (&c)[16], float ik, float fb, bool first) {
    const uint4 x = lds128(xp), y = lds128(xp + 2048);
    uint32_t w[8] = {x.x, x.y, x.z, x.w, y.x, y.y, y.z, y.w};
#pragma unroll
    for (int n = 0; n < 8; n++) {
        const float2 v = __half22float2(*reinterpret_cast<const __half2*>(&w[n]));
        w[n] = pack_bf16(fmaf(v.x, fb, c[2 * n] * ik), fmaf(v.y, fb, c[2 * n + 1] * ik));
    }
    stsm4(dst, w[0], w[1], w[2], w[3]);
    stsm4(dst + 1024, w[4], w[5], w[6], w[7]);
    __syncwarp();
    mbar_arrive_if(sb + MB_KT, first);
}
template <class F>
__device__ __forceinline__ void tpv_issue(float (&c)[16], const uint4 (&w0)[20], const uint4 (&w1)[20], int seg, uint64_t dbase, F mid) {
    dbase -= (seg & 1) * ((SM_XN - SM_XN2) >> 4);
    tp_issue<true, true, 0, V_SPLIT>(c, w0, SM_XN, dbase);
    if (!mid()) return;
    tp_issue<false, false, V_SPLIT, 20>(c, w0, SM_XN, dbase);
    tp_issue<false, true>(c, w1, SM_XN + 5 * 4096, dbase);
}
__device__ __forceinline__ void tpv_store(uint32_t dst, const float (&c)[16], float iv) {
    sts128(dst, pack_bf16(c[0] * iv, c[1] * iv), pack_bf16(c[2] * iv, c[3] * iv), pack_bf16(c[4] * iv, c[5] * iv), pack_bf16(c[6] * iv, c[7] * iv));
    sts128(dst + 2048, pack_bf16(c[8] * iv, c[9] * iv), pack_bf16(c[10] * iv, c[11] * iv), pack_bf16(c[12] * iv, c[13] * iv), pack_bf16(c[14] * iv, c[15] * iv));
}
__device__ __forceinline__ uint32_t hmul2(uint32_t a, uint32_t b) { uint32_t d; asm("mul.rn.f16x2 %0, %1, %2;" : "=r"(d) : "r"(a), "r"(b)); return d; }
__device__ __forceinline__ uint32_t hmax2abs(uint32_t a, uint32_t b) { uint32_t d; asm("max.xorsign.abs.f16x2 %0, %1, %2;" : "=r"(d) : "r"(a), "r"(b)); return d; }
__device__ __forceinline__ uint32_t hmax8abs(const uint4& m) { return hmax2abs(hmax2abs(m.x, m.y), hmax2abs(m.z, m.w)); }
__device__ __forceinline__ int out_scale(uint32_t sb, float usc, int lane) {
    const uint4 m0 = lds128(sb + SM_AM + lane * 16), m1 = lds128(sb + SM_AM + 512 + lane * 16);
    uint32_t a = hmax2abs(hmax8abs(m0), hmax8abs(m1));
    const uint2 c = lds64(sb + SM_CST + 32);
    a = __reduce_max_sync(~0u, hmax2abs(a, a >> 16) & 0x7fffu);
    return f16_exp(__uint_as_float(c.x) * fmaxf(__uint_as_float(c.y), 25.4f * usc * __half2float(__ushort_as_half((unsigned short)a))));
}

__device__ __forceinline__ int mem0_exp(const __nv_bfloat16* __restrict__ mem0, int lane) {
    uint32_t a = 0;
    uint4 y[20];
#pragma unroll
    for (int n = 0; n < 20; n++) y[n] = __ldg(reinterpret_cast<const uint4*>(mem0) + n * 32 + lane);
#pragma unroll
    for (int n = 0; n < 20; n++) a = absmax8(a, y[n]);
    return f16_exp(__uint_as_float(warp_absmax(a)));
}
__device__ __forceinline__ float mem0_frags(uint32_t sb, uint32_t mem, const __nv_bfloat16* __restrict__ mem0, int kh, int t, int lane) {
    const unsigned short* m0 = reinterpret_cast<const unsigned short*>(mem0) + (lane >> 2) * DM + 320 * kh + (lane & 3);
    uint32_t r[3][4];
#pragma unroll
    for (int n = 0; n < 3; n++) {
        const int u = min(t + 4 * n, 9);
#pragma unroll
        for (int i = 0; i < 4; i++) {
            const int d = n < 2 ? 16 * (u >> 1) + 64 * i + 4 * (u & 1) : 16 * i + 256 + 4 * (u - 8);
            r[n][i] = (uint32_t)__ldg(m0 + d) | ((uint32_t)__ldg(m0 + d + 8) << 16);
        }
    }
    const int ke = lds32(sb + SM_CST + (kh * 4 + t) * 4);
    const uint32_t s2 = (uint32_t)(127 + ke) * 0x00800080u, a = mem + (kh * 10 + t) * MV + (lane + (lane >> 3) * 2) * 16;
#pragma unroll
    for (int n = 0; n < 3; n++)
        if (n < 2 || t < 2) sts128(a + n * 4 * MV, bf16x2_to_f16x2p(r[n][0], s2), bf16x2_to_f16x2p(r[n][1], s2), bf16x2_to_f16x2p(r[n][2], s2), bf16x2_to_f16x2p(r[n][3], s2));
    return pow2i(-ke);
}
struct MemAddr {
    uint32_t wa0, wa2, r1;
    __device__ __forceinline__ void init(uint32_t mem, int kh, int t, int ln) {
        const uint32_t wa = mem + (kh * 10 + (ln >> 4)) * MV + (10 * (ln & 3) + ((ln >> 2) & 3)) * 16;
        wa0 = pin(wa + t * 2 * MV);
        wa2 = pin(kh ? t * 4096 + 2048 + 128 + ring_pos(ln >> 4) + (ln & 15) * 8 : wa + (8 + 10 * (t >> 1)) * MV + (t & 1) * 8);
        r1 = pin(t * 4096 + ring_pos(ln >> 3) + (ln & 7) * 16 + kh * 128);
    }
};
__device__ __forceinline__ unsigned char* ring_ptr(uint32_t r, int s, int j) {
    uint64_t p;
    asm("mov.b64 %0, {%1, %2};" : "=l"(p) : "r"(r | opaque((uint32_t)(uintptr_t)g_ring + (s & 1) * 512 + ((s & 2) + j) * 16384)), "r"((uint32_t)((uintptr_t)g_ring >> 32)));
    return reinterpret_cast<unsigned char*>(p);
}
struct MemWords {
    uint4 a, b, c, d;
    template <bool E>
    __device__ __forceinline__ void load(const unsigned char* p, const unsigned char* q) {
        a = ld_relaxed128(p); c = ld_relaxed128(p + 16384);
        if (E) { const uint2 x = ld_relaxed64(q), y = ld_relaxed64(q + 16384); b = make_uint4(x.x, x.y, 0, 0); d = make_uint4(y.x, y.y, 0, 0); }
        else { b = ld_relaxed128(p + 2048); d = ld_relaxed128(p + 16384 + 2048); }
    }
    template <bool E>
    __device__ __forceinline__ uint32_t missing() const { uint32_t x; asm("lop3.b32 %0, %1, %2, %3, 0x2a;" : "=r"(x) : "r"(a.w & c.w & (E ? b.y : b.w)), "r"(E ? d.y : d.w), "n"(CNT_FULL)); return x; }
    template <bool E>
    __device__ __forceinline__ void store(const MemAddr& ma, uint32_t z) const {
        if (E) { sts128(ma.wa0 + 64, a.z, b.x, c.z, d.x); sts128(ma.wa0, a.x, a.y, after(c.x, a.z, z), after(c.y, a.w, z)); }
        else {
            sts128(ma.wa0, a.x, a.y, a.z, after(c.z, a.w, z)); sts128(ma.wa0 + 64, b.x, b.y, b.z, after(d.z, b.w, z));
            sts64(ma.wa2, c.x, c.y); sts64(ma.wa2 + 64, d.x, d.y);
        }
    }
};
template <bool E>
__device__ __forceinline__ void fetch_issue(MemWords& m, int s, const MemAddr& ma, uint32_t tp, uint32_t d, uint32_t zr) {
    const unsigned char* p = ring_ptr(ma.r1, s - 1, 0), * q = ring_ptr(ma.wa2, s - 1, 0);
    sfence(zr);
    wait_clk(tp, d);
    m.load<E>(p, q);
}
template <bool E>
__device__ __forceinline__ void fetch_store(MemWords& m, int s, const MemAddr& ma, uint32_t zr, int fail) {
    if (s == 0) return;
    uint32_t n = 1;
    const uint32_t bad = m.missing<E>();
    if (SPEC_ST) m.store<E>(ma, zr);
    if (__any_sync(~0u, bad)) {
        const unsigned char* p = ring_ptr(ma.r1, s - 1, 0), * q = ring_ptr(ma.wa2, s - 1, 0);
#pragma unroll 1
        do {
            spin_guard(++n);
            m.load<E>(p, q);
        } while (__any_sync(~0u, m.missing<E>()));
        if (SPEC_ST) m.store<E>(ma, zr);
    }
    if (!SPEC_ST) m.store<E>(ma, zr);
}

__device__ __forceinline__ uint32_t* stamp_ptr(int h) { return g_stamp + (h >> 2) * 256 + (h & 3) * 4; }
__device__ __forceinline__ uint32_t stamp(int s, int ns) { return ((uint32_t)gtime64() + ns) * 64 + s + 1; }
__device__ __forceinline__ void post_time(int h, int r, int s, int ns, bool c) {
    asm volatile("{.reg .pred p; setp.ne.u32 p, %2, 0; @p st.relaxed.gpu.global.u32 [%0], %1;}" :: "l"(stamp_ptr(h) + r), "r"(stamp(s, ns)), "r"((uint32_t)c) : "memory");
}
__device__ __forceinline__ int lead_time(int h, uint32_t own, int lane) {
    int late;
#pragma unroll 1
    for (int n = 0; n < 16; n++) {
        const uint4 x = ld_relaxed128(stamp_ptr(lane));
        const uint32_t d0 = x.x - own, d1 = x.y - own, d2 = x.z - own;
        late = max(max((d0 & 63) ? 0 : (int)d0, (d1 & 63) ? 0 : (int)d1), (d2 & 63) ? 0 : (int)d2);
        if (__all_sync(~0u, ((d0 | d1 | d2) & 63) == 0)) break;
    }
    return max(min((__reduce_max_sync(~0u, late) - __shfl_sync(~0u, late, h)) >> 6, 1200) * 452 / 256 - SIG_DEAD, 0);
}

#define zr P.zero
__device__ __forceinline__ void vs_main(uint32_t sb, int h_, int w_, int lane_, const Ptrs& P, const Maps* maps) {
    float usc;
    lane_ = __shfl_sync(~0u, lane_, lane_);
    const uint32_t cfg_ = __shfl_sync(~0u, w_ | h_ << 3, 0);
    float iv;
    uint4 w0[20], w1[20];
    float c[16];
    auto to0 = [](uint32_t a) { return a ^ 2 * SM_RANK; };
    auto to1 = [](uint32_t a) { return (a & (SM_RANK - 1)) | SM_RANK; };
    const uint32_t vr = sb + SM_VR + (w_ & 1) * 4096 + (w_ >> 1) * 512 + lane_ * 16;
    auto send_v = [&](int g, uint32_t slot) {
        const uint32_t src = sb + SM_VR + slot, dst = sb + ((g & 1) ? SM_VX2 : SM_VX);
        fence_async_smem();
        asm volatile("{.reg .pred p; elect.sync _|p, 0xffffffff;\n@p cp.async.bulk.shared::cluster.shared::cta.mbarrier::complete_tx::bytes [%0], [%4], 8192, [%1];\n"
                     "@p cp.async.bulk.shared::cluster.shared::cta.mbarrier::complete_tx::bytes [%2], [%4], 8192, [%3];}"
                     :: "r"(to0(dst)), "r"(to0(sb) + MB_VX), "r"(to1(dst)), "r"(to1(sb) + MB_VX), "r"(src) : "memory");
    };

    {
        const int lane = lane_, t = cfg_ & 3, kh = (cfg_ >> 2) & 1;
        usc = mem0_frags(sb, sb + SM_MEMV, P.mem0, kh, t, lane);
        const uint32_t slot = sb + STG_V + 4 * kh * 20480;
        uint32_t a = 0;
        int k0 = 0, k1 = 0;
#pragma unroll 1
        for (int n = 0; n < 2; n++) {
#pragma unroll
            for (int k = 0; k < 20; k++) w0[k] = w1[k];
            k0 = k1;
            mbar_wait(sb + MB_PF + (4 * kh + 2 * n) * 8, 0); mbar_wait(sb + MB_PF + (4 * kh + 2 * n + 1) * 8, 0);
            a = max(a, load_tile(w1, k1, slot + n * 40960, 20480, 2 * t, lane, zr, [](uint32_t) {}));
        }
        if (lane == 0) { atomicMax(launch_flags() + F_WV, a); mbar_arrive(sb + MB_OM); }
        if (k0 != k1) {
            const int km = min(k0, k1);
            const uint32_t f0 = (uint32_t)max(15 + km - k0, 0) * 0x04000400u, f1 = (uint32_t)max(15 + km - k1, 0) * 0x04000400u;
#pragma unroll
            for (int k = 0; k < 20; k++) {
                w0[k].x = hmul2(w0[k].x, f0); w0[k].y = hmul2(w0[k].y, f0); w0[k].z = hmul2(w0[k].z, f0); w0[k].w = hmul2(w0[k].w, f0);
                w1[k].x = hmul2(w1[k].x, f1); w1[k].y = hmul2(w1[k].y, f1); w1[k].z = hmul2(w1[k].z, f1); w1[k].w = hmul2(w1[k].w, f1);
            }
            k0 = km;
        }
        iv = pow2i(-k0);
        bar_sync(BAR_ALL, 256);
        if (w_ == 0 && lane == 0) GTM(5);
        mbar_arrive_if(sb + MB_GO, lane == 0);
        mbar_arrive_remote_if(to0(sb) + MB_RDY, w_ == 0 && lane_ == 0); mbar_arrive_remote_if(to1(sb) + MB_RDY, w_ == 0 && lane_ == 0);
#pragma unroll 1
        for (int g = 0;; g++) {
            mbar_wait(sb + (g ? MB_XN2 : MB_XN), 0);
            if (g) bar_sync(BAR_ALL, 256);
            tpv_issue(c, w0, w1, g, P.desc, [] { return true; });
            if (g) break;
            wg_wait<0>();
            mbar_arrive_if(sb + MB_XNF, lane == 0);
            tpv_store(vr, c, iv);
        }
        mbar_wait(sb + MB_RDY, 0);
        if (w_ == 0) send_v(0, 0);
        if (w_ == 0 && lane == 0) GTM(7);
    }
    sb = __reduce_max_sync(~0u, sb);
    const int w = __reduce_max_sync(~0u, w_), h = __reduce_max_sync(~0u, h_);
    MemAddr ma;
    ma.init(sb + SM_MEMV, w >> 2, w & 3, lane_);
    const uint32_t memr = pin(sb + SM_MEMV + (lane_ + (lane_ >> 3) * 2) * 16), b8w = pin(sb + lane_ * 8 + (w & 1) * 1024 + (w >> 1) * 256);
    uint32_t vslot = 0, c0 = clk() - POLL_DELAY;
    sfence(zr & (memr ^ b8w ^ ma.r1 ^ ma.wa0 ^ ma.wa2));
#pragma unroll 1
    for (int s = 0;; s++) {
        const uint32_t ph = s & 1;
        const bool lane0 = (b8w & 255) == 0, first = lane0 && w == 0;
        if (s + 1 >= NVR) wait_att(sb, s + 1 - NVR);
        mbar_arrive_tx_if(sb + MB_R, 12, first && s < NSEG - 1);
        if (s + 2 < NSEG && w == 2) mbar_wait(sb + MB_XN + ph * (MB_XN2 - MB_XN), ((s >> 1) + 1) & 1);
        vslot = vslot == (NVR - 1) * 8192 ? 0 : vslot + 8192;
        if (V_ST_FIRST) { wg_wait<0>(); tpv_store(2 * b8w + opaque(vslot + SM_VR - sb + (w & 1) * 2048), c, iv); }
        MemWords mw;
        if (w >= 4) fetch_issue<true>(mw, s, ma, c0, 0, zr); else fetch_issue<false>(mw, s, ma, c0, POLL_DELAY - POLL_EARLY, zr);
        sfence(zr);
        if (!V_ST_FIRST) { wg_wait<0>(); tpv_store(2 * b8w + opaque(vslot + SM_VR - sb + (w & 1) * 2048), c, iv); sfence(zr); }
        if (w >= 4) { fetch_store<true>(mw, s, ma, zr, s < 4 ? -1 : 3); bar_sync(BAR_MEM + 1, 128); }
        else { fetch_store<false>(mw, s, ma, zr, s < 4 ? -1 : 2); bar_sync(BAR_MEM, 256); }
        uint4 mb[20];
        float p0[4] = {0, 0, 0, 0}, p1[4] = {0, 0, 0, 0}, p2[4] = {0, 0, 0, 0}, p3[4] = {0, 0, 0, 0};
        auto vec = [](int u) { return u < 8 ? 10 + u : u < 18 ? u - 8 : u; };
#pragma unroll
        for (int u = 0; u < V_DEPTH; u++) mb[u] = lds128(memr + vec(u) * MV);
        post_time(h, 2, s, SIG_V, first);
        sfence(zr);
#pragma unroll
        for (int u = 0; u < 20; u++) {
            const int v = vec(u);
            const uint4 &a = v < 10 ? w0[2 * v % 20] : w1[2 * v % 20], &b = v < 10 ? w0[2 * v % 20 + 1] : w1[2 * v % 20 + 1];
            if (u & 1) { mma16816h(p2, a, mb[u].x, mb[u].y); mma16816h(p3, b, mb[u].z, mb[u].w); }
            else { mma16816h(p0, a, mb[u].x, mb[u].y); mma16816h(p1, b, mb[u].z, mb[u].w); }
            if (u + V_DEPTH < 20) sfence(zr);
            if (u + V_DEPTH == 8) bar_sync_if(BAR_MEM, 256, w >= 4);
            if (u + V_DEPTH < 20) mb[u + V_DEPTH] = lds128(memr + vec(u + V_DEPTH) * MV);
            if (u == PH_AT) sts32_if(sb + SM_PH, 2 * s + 1, lane0 && w == PH_W);
        }
        const float f = iv * usc;
        const uint32_t y0 = pack_bf16(fmaf(p2[0] + p3[0], f, (p0[0] + p1[0]) * f), fmaf(p2[1] + p3[1], f, (p0[1] + p1[1]) * f));
        const uint32_t y1 = pack_bf16(fmaf(p2[2] + p3[2], f, (p0[2] + p1[2]) * f), fmaf(p2[3] + p3[3], f, (p0[3] + p1[3]) * f));
        st_async64(b8w + opaque(to0(sb) - sb + SM_VM + (s & zr)), y0, y1, to0(sb) + MB_V);
        st_async64(b8w + opaque(SM_BASE + SM_RANK - sb + SM_VM + (s & zr)), y0, y1, SM_BASE + SM_RANK + MB_V);
        sts64(b8w + SM_KM + (s % NKM) * 4096 + 2048, y0, y1);
KMDUMP(        *reinterpret_cast<uint2*>(g_kmd + (uint32_t)((h * NSEG + s) * 4096 + 2048 + w * 256 + lane_ * 8)) = make_uint2(y0, y1);)
        if (w == 7 && s + 3 < NSEG) {
            if (s == 1) mbar_wait(sb + MB_CST, 0);
            if (s < 2) fence_async();
            tma_xn(sb + SM_XN2 + ph * (SM_XN - SM_XN2), &maps->xnp, s + 3, sb + MB_XN2 - ph * (MB_XN2 - MB_XN));
        }
        bar_sync(BAR_ALL, 256);
        mbar_arrive_tx_if(sb + MB_KM + (s & 7) * 8, 2048, first);
        sts32_if(sb + SM_PH, 2 * s + 2, first);
        if (w == 0) VT(s, 0);
        if (__builtin_expect(s == NSEG - 1, 0)) break;
        tpv_issue(c, w0, w1, s, P.desc, [&] { if (w == 1 && s + 2 < NSEG) send_v(s + 1, vslot); return s + 2 < NSEG; });
        mbar_wait(sb + MB_R, ph);
        c0 = clk();
        { const uint4 cp = lds128(sb + SM_RC); c0 += min(max((int)(cp.x + cp.z - c0), -POLL_DELAY), POLL_MAX); usc = uf(cp.y); }
    }
}

template <bool ISA>
__device__ __forceinline__ void load_wo(uint32_t sb, uint4 (&wx)[X_RES], int j, int t, int lane, const Ptrs& P) {
    constexpr int NOT = ISA ? 3 : 2, NSW = ISA ? A_SW : B_SW;
    const int m = lane >> 3, sg = lane & 7;
    uint4 wo[NOT * 8];
#pragma unroll
    for (int i = 0; i < NOT; i++) {
        const int co = (ISA && j && i < 2 ? 32 * t + 16 * i : 16 * t + 64 * (i + (ISA ? 0 : 3))) + 8 * (m & 1);
        const uint32_t base = sb + STG_O + (co >> 6) * 16384 + (8 * (m >> 1) + sg) * 128 + ((((co & 63) >> 3) ^ sg) << 4);
#pragma unroll
        for (int T = 0; T < 8; T++) wo[T * NOT + i] = ldsm4t(base + T * 2048);
    }
    uint32_t all = 0;
#pragma unroll
    for (int f = 0; f < NOT * 8; f++) all = absmax8(all, wo[f]);
    all = warp_absmax(all);
    if (lane == 0) { atomicMax(launch_flags() + F_WO, all); mbar_arrive(sb + MB_OM); }
    bar_sync(after(BAR_ALL, all, zr), 256);
#pragma unroll
    for (int f = 0; f < X_RES; f++) wx[f] = wo[NSW + f];
#pragma unroll
    for (int f = 0; f < NSW; f++) sts128(sb + lane * 16 + SM_FO + t * 512 + ((ISA ? 0 : A_SW) + f) * 2048, wo[f]);
}
template <bool ISA>
__device__ __forceinline__ void chain_loop(uint32_t sb, int h, int j, int t, int lane, const Ptrs& P, uint4 (&wq)[20], const uint4 (&wk)[20], const uint4 (&wx)[X_RES],
                                           float (&c)[16], float usc, float iq, float ik);
__device__ __forceinline__ void chain_main(uint32_t sb, int h, int j, int w_, int lane_, const Ptrs& P) {
    lane_ = __shfl_sync(~0u, lane_, lane_);
    const int w = __reduce_max_sync(~0u, w_), kh = w >> 2, t = w & 3, lane = lane_;
    float iq, ik;
    float c[16];
    uint4 wq[20], wk[20], wx[X_RES];
#pragma unroll 1
    for (int i = 0; i < 5; i++) mbar_wait(sb + MB_PO + i * 8, 0);
    if (w == 0 && lane == 0) GTM(3);
    if (kh == 0) load_wo<true>(sb, wx, j, t, lane, P); else load_wo<false>(sb, wx, j, t, lane, P);
    const float usc = mem0_frags(sb, sb + SM_MEM, P.mem0, kh, t, lane);
#pragma unroll 1
    for (int n = 0; n < 2; n++) {
        const int c0 = 4 * n + 2 * kh;
        const uint32_t s0 = sb + STG_QK + (c0 % 5) * 20480, ds = ((c0 + 1) % 5 - c0 % 5) * 20480;
        mbar_wait(sb + MB_PF + c0 * 8, 0); mbar_wait(sb + MB_PF + c0 * 8 + 8, 0);
        int kw;
        load_tile(wq, kw, s0, ds, 2 * t, lane, zr, [&](uint32_t d) { mbar_arrive_if(after(sb + MB_PE + kh * 8, d, zr), lane == 0 && n == 0); });
        iq = pow2i(-kw);
        if (n) break;
        ik = iq;
#pragma unroll
        for (int k = 0; k < 20; k++) wk[k] = wq[k];
        if (w == 0 && lane == 0) GTM(4);
#pragma unroll 1
        for (int g = 0;; g++) {
            mbar_wait(sb + MB_XN, g);
            tp_issue<true, true, 0, B_SPLIT>(c, wk, SM_XN + kh * 5 * 4096, P.desc);
            if (g) break;
            tp_issue<false, true, B_SPLIT, 20>(c, wk, SM_XN + kh * 5 * 4096, P.desc);
            wg_wait<0>();
            mbar_arrive_if(sb + MB_XNF, lane == 0);
            if (kh) { tp_dump_k(sb + t * 512 + lane * 16 + SM_XP, c); sts32(sb + SM_IK + t * 4, __float_as_uint(ik * 512)); }
            bar_sync(BAR_PAIR + t, 64);
            if (!kh) tp_combine_k(sb, sb + t * 512 + lane * 16 + SM_XP, kt_lane(sb, t, lane) + SM_KT0, c, ik, uf(lds32(sb + SM_IK + t * 4)), lane == 0);
        }
        wg_wait<0>();
    }
    bar_sync(BAR_ALL, 256);
    if (w == 0 && lane == 0) GTM(5);
    iq *= 0.08838834764831845f * 1.4426950408889634f;
    if (kh == 0) chain_loop<true>(sb, h, j, t, lane, P, wq, wk, wx, c, usc, iq, ik);
    else chain_loop<false>(sb, h, j, t, lane, P, wq, wk, wx, c, usc, iq, ik);
}
template <bool ISA>
__device__ __forceinline__ void chain_loop(uint32_t sb, int h, int j, int t, int lane, const Ptrs& P, uint4 (&wq)[20], const uint4 (&wk)[20], const uint4 (&wx)[X_RES],
                                           float (&c)[16], float usc, float iq, float ik) {
    constexpr int KH = ISA ? 0 : 1;
    constexpr int NOT = ISA ? 3 : 2;
    constexpr int NRES = ISA ? A_RES : B_RES, NSW = NOT * 8 - NRES, NDISP = ISA ? A_DISP : B_DISP, DEPTH = ISA ? A_DEPTH : B_DEPTH;
    constexpr int FO = SM_FO + (ISA ? 0 : A_SW) * 2048, FQ = SM_FQ + (ISA ? 0 : A_DISP) * 2048;
    const uint32_t b0l = pin(sb + lane * 16), bt = pin(sb + lane * 16 + t * 512), b8l = pin(sb + lane * 8), b8t = pin(sb + lane * 8 + t * 256);
    const uint32_t memr = pin(sb + SM_MEM + KH * 10 * MV + (lane + (lane >> 3) * 2) * 16);
    const uint32_t mat = !ISA ? 0 : pin(sb + SM_QM + (lane & 7) * 16 + (lane < 16 ? (t >> 1) * 512 + (t & 1) * 128 + (lane & 8) * 32 : 1024 + t * 512 + (lane & 8) * 16));
#pragma unroll
    for (int k = 0; k < NDISP; k++) sts128(bt + FQ + k * 2048, wq[k]);
    if (ISA) { sts128(sb + SM_ONE, BF_ONES, BF_ONES, BF_ONES, BF_ONES); sts32(sb + SM_USC + 4, 63); }
    bar_sync(BAR_ALL, 256);
    if (ISA && t == 0 && lane == 0) GTM(7);
    const uint32_t rv = __reduce_max_sync(~0u, lds32(sb + SM_RV + 4));
    const uint32_t rdelta = __reduce_max_sync(~0u, (j ? rv ^ 2 * SM_RANK : SM_BASE + SM_RANK) - sb), rdelta2 = __reduce_max_sync(~0u, rv - sb);
    if (ISA) { mbar_arrive_remote_if(sb + rdelta + MB_RDY, t == 0 && lane == 0); mbar_arrive_remote_if(sb + rdelta2 + MB_RDY, t == 0 && lane == 0); }
    mbar_wait(sb + MB_RDY, 0);
    const uint32_t srem = ISA ? pin(b8t + rdelta + SM_SREM) : 0, mrem = ISA ? pin(sb + rdelta + MB_S) : 0;
    if (ISA) mbar_wait(sb + MB_KTF, 0);
    const float fb = ISA ? uf(__reduce_max_sync(~0u, lds32(sb + SM_IK + t * 4))) : 0;
    uint4 wr_[NRES];
#pragma unroll
    for (int f = 0; f < NRES; f++) wr_[f] = f < NRES - X_RES ? lds128(bt + FO + (NSW + f) * 2048) : wx[f < NRES - X_RES ? 0 : f - (NRES - X_RES)];
    MemAddr ma;
    ma.init(sb + SM_MEM, KH, t, lane);
    constexpr int RL = ISA ? A_RL : B_RL, RL2 = ISA ? A_RL2 : NDISP, SPLIT = ISA ? A_SPLIT : B_SPLIT;
    if (SPLIT > B_SPLIT) tp_issue<false, true, B_SPLIT, SPLIT>(c, wk, SM_XN + KH * 5 * 4096, P.desc);
    uint32_t c0 = clk() - POLL_DELAY;
    sfence(zr & (wr_[0].x ^ wr_[1].x ^ wr_[2].x ^ wr_[3].x ^ ma.wa0 ^ memr ^ b0l ^ b8l ^ b8t ^ mat ^ srem ^ mrem ^ ma.r1 ^ ma.wa2));

#pragma unroll 1
    for (int s = 0;; s++) {
        const uint32_t ph = s & 1;
        const bool first = (b8l & 255) == 0;
        MemWords mw;
        fetch_issue<!ISA>(mw, s, ma, c0, ISA ? POLL_DELAY : POLL_EARLY, zr);
        sfence(zr);
        if (SPLIT < 20) tp_issue<false, true, SPLIT, 20>(c, wk, SM_XN + KH * 5 * 4096, P.desc);
#pragma unroll
        for (int kk = RL; kk < RL2; kk++) wq[kk] = lds128(bt + FQ + kk * 2048);
        wg_wait<0>();
        mbar_arrive_if(sb + MB_XNF, first);
        if (ISA) {
            bar_sync(BAR_PAIR + t, 64);
            tp_combine_k(sb, bt + SM_XP, b0l + (b0l & 256) + opaque((t >> 1) * 2048 + (t & 1) * 256 + SM_KT1 - ph * (SM_KT1 - SM_KT0)), c, ik, fb, first && s < NSEG - 1);
        } else { tp_dump_k(bt + SM_XP, c); bar_arrive(BAR_PAIR + t, 64); }
        sfence(zr);
        if (RL2 < NDISP) {
#pragma unroll
            for (int kk = RL2; kk < NDISP; kk++) wq[kk] = lds128(bt + FQ + kk * 2048);
            sfence(zr);
        }
        fetch_store<!ISA>(mw, s, ma, zr, s < 4 ? -1 : KH);
        if (ISA) bar_arrive(BAR_LATE, 256);
        bar_sync(BAR_MEM + KH, ISA && B_GO >= 0 ? 256 : 128);
        float q[4] = {0, 0, 0, 0}, k[4] = {0, 0, 0, 0}, q2[4] = {0, 0, 0, 0}, k2[4] = {0, 0, 0, 0};
        uint4 mb[10], wo[NOT * 8], kx0, kx1, pq, pk;
#pragma unroll
        for (int u = 0; u < DEPTH; u++) mb[u] = lds128(memr + u * MV);
        sfence(zr);
#pragma unroll
        for (int u = 0; u < 10; u++) {
            mma16816h(q2, wq[2 * u], mb[u].x, mb[u].y);
            mma16816h(k2, wk[2 * u], mb[u].x, mb[u].y);
            mma16816h(q, wq[2 * u + 1], mb[u].z, mb[u].w);
            mma16816h(k, wk[2 * u + 1], mb[u].z, mb[u].w);
            if (u == 0) TS(KH, 0, mb[0].x);
            sfence(zr);
            if (u + DEPTH < (ISA ? 10 : 8)) mb[u + DEPTH] = lds128(memr + (u + DEPTH) * MV);
            if (u == 0) mbar_arrive_if(sb + MB_MEM, first && s > 0);
            if (!ISA && u == B_GO) bar_arrive(BAR_MEM, 256);
            if (!ISA && u == LATE_AT) { bar_sync(BAR_LATE, 256); mb[8] = lds128(memr + 8 * MV); mb[9] = lds128(memr + 9 * MV); post_time(h, j, s, 0, first && t == 3); sfence(zr); }
            if (ISA && u == KX_AT) kx0 = ldsm4t(bt + (SM_KT0 + ph * (SM_KT1 - SM_KT0)));
            if (ISA && u == KX_AT + 1) kx1 = ldsm4t(bt + (SM_KT0 + ph * (SM_KT1 - SM_KT0)) + 2048);
            if (ISA && u == PQ_AT) { bar_sync(BAR_PAIR + t, 64); pq = lds128(bt + SM_XQ); pk = lds128(bt + SM_XQ + 2048); sfence(zr); }
        }
        float l0, l1;
        const float fq = usc * iq, fk = usc * ik;
        auto scores = [&](uint32_t a, const uint4& y0, const uint4& y1, auto mid) {
            const uint4 x0 = ldsm4t(b0l + SM_QM), x1 = ldsm4t(b0l + SM_QM + 512);
            mid();
            float z[4][4];
#pragma unroll
            for (int n = 0; n < 4; n++) z[n][0] = z[n][1] = z[n][2] = z[n][3] = 0;
            mma16816(z[0], x0, y0.x, y0.y); mma16816(z[1], x0, y0.z, y0.w); mma16816(z[2], x1, y1.x, y1.y); mma16816(z[3], x1, y1.z, y1.w);
            const float z0 = (z[0][0] + z[1][2]) + (z[2][0] + z[3][2]), z1 = (z[0][1] + z[1][3]) + (z[2][1] + z[3][3]);
            const uint32_t e0 = exp_or_mark(z0), e1 = exp_or_mark(z1);
            if (ISA) st_async64(srem, e0, e1, mrem); else st_async64(a + opaque(rdelta + SM_SREM + (s & zr)), e0, e1, sb + rdelta + MB_S);
            sts64(a + SM_SLOC, e0, e1);
            return make_uint2(e0, e1);
        };
        auto publish = [&]() {
            const uint2 km = ldsm2t(bt + SM_KMM);
            st_async64(b8t + opaque(rdelta2 + SM_KM + (s % NKM) * 4096 + j * 1024), km.x, km.y, rv + MB_KM + (s & 7) * 8);
KMDUMP(            *reinterpret_cast<uint2*>(g_kmd + (uint32_t)((h * NSEG + s) * 4096 + (4 * j + t) * 256 + lane * 8)) = km;)
            mbar_arrive_if(sb + MB_PUB + ph * 8, first);
        };
        if (ISA) {
            stsm4(mat,
                  pack_bf16(fmaf(q[0], fq, fmaf(q2[0], fq, uf(pq.x))), fmaf(q[1], fq, fmaf(q2[1], fq, uf(pq.y)))), pack_bf16(fmaf(q[2], fq, fmaf(q2[2], fq, uf(pq.z))), fmaf(q[3], fq, fmaf(q2[3], fq, uf(pq.w)))),
                  pack_bf16(fmaf(k[0], fk, fmaf(k2[0], fk, uf(pk.x))), fmaf(k[1], fk, fmaf(k2[1], fk, uf(pk.y)))), pack_bf16(fmaf(k[2], fk, fmaf(k2[2], fk, uf(pk.z))), fmaf(k[3], fk, fmaf(k2[3], fk, uf(pk.w)))));
            bar_sync(BAR_RED, 192);
            uint4 vx[4];
            const uint2 own = scores(b8t, kx0, kx1, [&] {
                sfence(zr);
#pragma unroll
                for (int i = 0; i < VX_PRE; i++) vx[i] = lds128(bt + (SM_VX + ph * 8192) + i * 2048);
                sfence(zr);
            });
            TS(0, 1, 0);
            bar_sync(BAR_BGO, 288);
            if (s == NSEG - 1) { mbar_wait(sb + MB_S, 1); mbar_wait(sb + MB_V, 1); break; }
            uint2 lo[5];
#pragma unroll
            for (int i = 0; i < 5; i++) lo[i] = lds64(b8l + SM_SLOC + i * 256);
            const uint4 one = lds128(sb + SM_ONE);
#pragma unroll
            for (int i = VX_PRE; i < 4; i++) vx[i] = lds128(bt + (SM_VX + ph * 8192) + i * 2048);
#pragma unroll
            for (int f = 0; f < A_P1; f++) wo[f] = lds128(bt + FO + f * 2048);
            sfence(zr);
            uint32_t neg = ((lo[0].x | lo[0].y | lo[1].x) | (lo[1].y | lo[2].x | lo[2].y) | (lo[3].x | lo[3].y) | (lo[4].x | lo[4].y));
            mbar_wait(sb + MB_S, ph);
            TS(0, 2, 0);
            uint2 r[5];
#pragma unroll
            for (int i = 0; i < 5; i++) r[i] = lds64(b8l + SM_SREM + i * 256);
            const uint32_t vok = mbar_try(sb + MB_V, ph);
            neg = (neg | own.x | own.y) & 0x80000000u;
            uint32_t p[5];
#pragma unroll
            for (int i = 0; i < 5; i++) p[i] = pack_bf16(uf(lo[i].x) * uf(r[i].x), uf(lo[i].y) * uf(r[i].y));
            neg = (opaque(opaque(neg | p[0] | p[1]) | p[2] | p[3]) | p[4]) & 0x80008000u;
            if (__builtin_expect(__any_sync(~0u, neg || !vok), 0)) {
                mbar_wait(sb + MB_V, ph);
                if (__any_sync(~0u, neg)) {
                    float sv[10], mx = -INFINITY;
#pragma unroll
                    for (int i = 0; i < 10; i++) {
                        const uint32_t a = lds32(b8l + SM_SLOC + (i >> 1) * 256 + (i & 1) * 4), b = lds32(b8l + SM_SREM + (i >> 1) * 256 + (i & 1) * 4);
                        sv[i] = ((int)a < 0 ? uf(a << 1) : lg2(uf(a))) + ((int)b < 0 ? uf(b << 1) : lg2(uf(b)));
                        mx = fmaxf(mx, sv[i]);
                    }
                    mx = fmaxf(mx, __shfl_xor_sync(~0u, mx, 1));
                    mx = fmaxf(mx, __shfl_xor_sync(~0u, mx, 2));
#pragma unroll
                    for (int i = 0; i < 5; i++) p[i] = pack_bf16(ex2(sv[2 * i] - mx), ex2(sv[2 * i + 1] - mx));
                }
            }
            const uint2 vm0 = lds64(b8t + SM_VM), vm1 = lds64(b8t + SM_VM + 1024);
            float o0[4] = {0, 0, 0, 0}, o1[4] = {0, 0, 0, 0}, ls[4] = {0, 0, 0, 0};
            mma16816(o0, vx[0], p[0], p[1]); mma16816(o1, vx[2], p[0], p[1]);
            mma16816(ls, one, p[0], p[1]);
            sfence(zr);
#pragma unroll
            for (int f = A_P1; f < A_P2; f++) wo[f] = lds128(bt + FO + f * 2048);
            sfence(zr);
            mma16816(o0, vx[1], p[2], p[3]); mma16816(o1, vx[3], p[2], p[3]);
            mma16816(ls, one, p[2], p[3]);
            mma1688(o0, vm0.x, vm0.y, p[4]); mma1688(o1, vm1.x, vm1.y, p[4]);
            mma1688(ls, one.x, one.y, p[4]);
            stsm4(bt + SM_OB, pack_bf16(o0[0], o0[1]), pack_bf16(o0[2], o0[3]), pack_bf16(o1[0], o1[1]), pack_bf16(o1[2], o1[3]));
            l0 = ls[0]; l1 = ls[1];
            sts64(b8t + SM_LS, __float_as_uint(l0), __float_as_uint(l1));
        } else {
            sts128f(bt + SM_XQ, fmaf(q[0], fq, q2[0] * fq), fmaf(q[1], fq, q2[1] * fq), fmaf(q[2], fq, q2[2] * fq), fmaf(q[3], fq, q2[3] * fq));
            sts128f(bt + SM_XQ + 2048, fmaf(k[0], fk, k2[0] * fk), fmaf(k[1], fk, k2[1] * fk), fmaf(k[2], fk, k2[2] * fk), fmaf(k[3], fk, k2[3] * fk));
            bar_arrive(BAR_PAIR + t, 64);
            sfence(zr);
            {
                uint4 m[5];
#pragma unroll
                for (int i = 0; i < 5; i++) m[i] = lds128(memr + opaque((5 * t - 10) * MV + (s & zr)) + i * MV);
                sts64(b8t + SM_AM, hmax2abs(hmax8abs(m[0]), hmax8abs(m[1])), hmax2abs(hmax2abs(hmax8abs(m[2]), hmax8abs(m[3])), hmax8abs(m[4])));
                sfence(zr);
            }
            {
                uint32_t fa = bt;
#pragma unroll
                for (int f = 0; f < B_P1; f++) { wo[f] = lds128(fa + FO + f * 2048); if (f % P1_ILP == P1_ILP - 1) fa = after(bt, wo[f].x, zr); }
            }
            if (t == 0) { bar_sync(BAR_RED, 192); const uint4 y0 = ldsm4t(b0l + (b0l & 256) + SM_KMM), y1 = ldsm4t(b0l + (b0l & 256) + SM_KMM + 1024); scores(b8l + 1024, y0, y1, [] {}); }
            bar_sync(BAR_BGO, 288);
            if (s == NSEG - 1) { publish(); break; }
            if (!PUB_RED) { publish(); sfence(zr); }
            {
                uint32_t fa = bt;
#pragma unroll
                for (int f = B_P1; f < B_P2; f++) { wo[f] = lds128(fa + FO + f * 2048); if ((f - B_P1) % PRE_ILP == PRE_ILP - 1) fa = after(bt, wo[f].x, zr); }
            }
        }
        unsigned char* wr1 = ring_ptr(ma.r1, s, j), * wr2 = ring_ptr(ma.wa2, s, j);
        if (!ISA) {
            uint32_t x = 0;
#pragma unroll
            for (int f = 0; f < B_P2; f++) x |= wo[f].x;
            sfence(zr & x);
        }
        bar_sync(BAR_O, 288);
        float acc[NOT][4], acd[NOT][4];
#pragma unroll
        for (int i = 0; i < NOT; i++) { acc[i][0] = acc[i][1] = acc[i][2] = acc[i][3] = 0; acd[i][0] = acd[i][1] = acd[i][2] = acd[i][3] = 0; }
        {
            uint4 ob[4];
            ob[0] = ldsm4t(b0l + SM_OB);
            if (!ISA) { ob[1] = ldsm4t(b0l + SM_OB + 512); ob[2] = ldsm4t(b0l + SM_OB + 1024); }
            c0 = clk();
            if (ISA) ob[1] = ldsm4t(b0l + SM_OB + 512);
            else { const uint2 l = lds64(b8t + SM_LS); l0 = uf(l.x); l1 = uf(l.y); }
            usc = uf(lds32(b8l + SM_USC));
            sfence(zr);
#pragma unroll
            for (int T = 0; T < 8; T++) {
                const uint32_t b0 = (T & 1) ? ob[T >> 1].z : ob[T >> 1].x, b1 = (T & 1) ? ob[T >> 1].w : ob[T >> 1].y;
#pragma unroll
                for (int i = 0; i < NOT; i++) {
                    const int f = T * NOT + i;
                    const uint4& a = f >= NSW ? wr_[f >= NSW ? f - NSW : 0] : wo[f];
                    if (!(T & 1) && !ISA) mma16816(acd[i], a, b0, b1); else mma16816(acc[i], a, b0, b1);
                }
                if (ISA) {
                    if (T < 6) sfence(zr);
                    if (T == 1 || T == 3) { ob[T / 2 + 2] = ldsm4t(b0l + SM_OB + (T / 2 + 2) * 512); sfence(zr); }
#pragma unroll
                    for (int f = T ? A_P3 + 3 * T : A_P2; f < A_P3 + 3 * (T + 1) && f < NSW; f++) wo[f] = lds128(bt + FO + f * 2048);
                    if (T == 4) { l0 = rcp(l0 * usc); l1 = rcp(l1 * usc); }
                    if (T < 4) sfence(zr);
                } else if (T == 1) {
                    sfence(zr);
                    ob[3] = ldsm4t(b0l + SM_OB + 1536);
#pragma unroll
                    for (int f = B_P2; f < NSW; f++) wo[f] = lds128(bt + FO + f * 2048);
                    sfence(zr);
                } else if (T == 3) {
                    sfence(zr);
                    l0 = rcp(l0 * usc); l1 = rcp(l1 * usc);
                }
            }
#pragma unroll
            for (int i = 0; i < NOT; i++) {
                if (ISA) { acc[i][0] *= l0; acc[i][1] *= l1; acc[i][2] *= l0; acc[i][3] *= l1; }
                else { acc[i][0] = fmaf(acc[i][0], l0, acd[i][0] * l0); acc[i][1] = fmaf(acc[i][1], l1, acd[i][1] * l1); acc[i][2] = fmaf(acc[i][2], l0, acd[i][2] * l0); acc[i][3] = fmaf(acc[i][3], l1, acd[i][3] * l1); }
            }
        }
        if (ISA) {
            red_h8(wr1, pack_f16(acc[0][0], acc[0][2]), pack_f16(acc[1][0], acc[1][2]), pack_f16(acc[NOT - 1][0], acc[NOT - 1][2]), CNT_ONE);
            red_h8(wr1 + 2048, pack_f16(acc[0][1], acc[0][3]), pack_f16(acc[1][1], acc[1][3]), pack_f16(acc[NOT - 1][1], acc[NOT - 1][3]), CNT_ONE);
        } else {
            red_h8(wr1, pack_f16(acc[0][0], acc[0][2]), pack_f16(acc[1][0], acc[1][2]), pack_f16(acc[0][1], acc[0][3]), CNT_ONE);
            red_h4(wr2, pack_f16(acc[1][1], acc[1][3]), CNT_ONE);
            if (PUB_RED) { sfence(zr); publish(); }
        }
        TS(KH, 3, __float_as_uint(acc[0][0]));
        bar_sync(BAR_PW, 288);
#pragma unroll
        for (int kk = 0; kk < RL; kk++) wq[kk] = lds128(bt + FQ + kk * 2048);
        tp_issue<true, true, 0, SPLIT>(c, wk, SM_XN + KH * 5 * 4096, P.desc);
        sfence(zr);
        { uint32_t x, n = 0; while (((x = lds32(sb + SM_USC + 4)) ^ s) & 63) spin_guard(++n >> 2); c0 += x >> 6; }
    }
#undef zr
}

template <class F>
__device__ __forceinline__ void att_pass(uint32_t rec, uint32_t out, uint32_t vt, uint32_t kmr, int up, int lane, F half) {
    float sc[5][4];
#pragma unroll
    for (int i = 0; i < 5; i++) sc[i][0] = sc[i][1] = sc[i][2] = sc[i][3] = 0;
    const uint32_t rl = rec + lane * 16, kl = rec + REC_K + (lane >> 4) * 512 + (lane & 15) * 16;
#pragma unroll S_UNROLL
    for (int T = 0; T < 8; T++) {
        const uint4 q = lds128(rl + REC_Q + up * 4096 + T * 512), k1 = ldsm4t(kl + (T >> 1) * 2048 + (T & 1) * 256 + up * 1024);
        const uint2 km = lds64(kmr + T * 256);
        mma16816(sc[3], q, k1.x, k1.y); mma16816(sc[4], q, k1.z, k1.w);
        mma16816(sc[0], q, km.x, km.y);
        if (up) { const uint4 k0 = ldsm4t(kl + (T >> 1) * 2048 + (T & 1) * 256); mma16816(sc[1], q, k0.x, k0.y); mma16816(sc[2], q, k0.z, k0.w); }
    }
    const int dg = (lane >> 2) - 2 * (lane & 3);
    if (dg < 0) sc[3][0] = sc[4][2] = -INFINITY;
    if (dg < 1) sc[3][1] = sc[4][3] = -INFINITY;
    sc[4][0] = sc[4][1] = -INFINITY;
    if (!up) {
#pragma unroll
        for (int i = 0; i < 4; i++) sc[1][i] = sc[2][i] = -INFINITY;
    }
    float m0 = fmaxf(sc[0][0], sc[0][1]), m1 = fmaxf(sc[0][2], sc[0][3]);
#pragma unroll
    for (int i = 1; i < 5; i++) { m0 = fmaxf(m0, fmaxf(sc[i][0], sc[i][1])); m1 = fmaxf(m1, fmaxf(sc[i][2], sc[i][3])); }
#pragma unroll
    for (int o = 1; o < 4; o <<= 1) { m0 = fmaxf(m0, __shfl_xor_sync(~0u, m0, o)); m1 = fmaxf(m1, __shfl_xor_sync(~0u, m1, o)); }
    uint32_t pl[5], ph[5];
    const float fq = 0.08838834764831845f * 1.4426950408889634f;
    m0 *= -fq; m1 *= -fq;
    float l0 = 0, l1 = 0;
#pragma unroll
    for (int i = 0; i < 5; i++) {
        sc[i][0] = ex2(fmaf(sc[i][0], fq, m0)); sc[i][1] = ex2(fmaf(sc[i][1], fq, m0)); sc[i][2] = ex2(fmaf(sc[i][2], fq, m1)); sc[i][3] = ex2(fmaf(sc[i][3], fq, m1));
        l0 += sc[i][0] + sc[i][1]; l1 += sc[i][2] + sc[i][3];
    }
#pragma unroll
    for (int o = 1; o < 4; o <<= 1) { l0 += __shfl_xor_sync(~0u, l0, o); l1 += __shfl_xor_sync(~0u, l1, o); }
    l0 = rcp(l0); l1 = rcp(l1);
#pragma unroll
    for (int i = 0; i < 5; i++) { pl[i] = pack_bf16(sc[i][0] * l0, sc[i][1] * l0); ph[i] = pack_bf16(sc[i][2] * l1, sc[i][3] * l1); }
    half();
    uint4 v[4][4];
    uint2 vm[4][2];
    auto fetch = [&](int n) {
        v[n][1] = lds128(vt + n * 512 + up * 2048); v[n][3] = lds128(vt + 4096 + n * 512 + up * 2048);
        v[n][0] = v[n][2] = make_uint4(0, 0, 0, 0);
        if (up) { v[n][0] = lds128(vt + n * 512); v[n][2] = lds128(vt + 4096 + n * 512); }
        vm[n][0] = lds64(kmr + 2048 + n * 256); vm[n][1] = lds64(kmr + 3072 + n * 256);
    };
    fetch(0);
#pragma unroll
    for (int n = 0; n < 4; n++) {
        if (n < 3) fetch(n + 1);
        float o[4][4];
#pragma unroll
        for (int i = 0; i < 4; i++) o[i][0] = o[i][1] = o[i][2] = o[i][3] = 0;
        mma16816(o[0], v[n][1], pl[3], pl[4]); mma16816(o[1], v[n][3], pl[3], pl[4]); mma16816(o[2], v[n][1], ph[3], ph[4]); mma16816(o[3], v[n][3], ph[3], ph[4]);
        if (up) { mma16816(o[0], v[n][0], pl[1], pl[2]); mma16816(o[1], v[n][2], pl[1], pl[2]); mma16816(o[2], v[n][0], ph[1], ph[2]); mma16816(o[3], v[n][2], ph[1], ph[2]); }
        mma1688(o[0], vm[n][0].x, vm[n][0].y, pl[0]); mma1688(o[1], vm[n][1].x, vm[n][1].y, pl[0]); mma1688(o[2], vm[n][0].x, vm[n][0].y, ph[0]); mma1688(o[3], vm[n][1].x, vm[n][1].y, ph[0]);
        const uint32_t d = out + (n >> 1) * 4096 + (n & 1) * 512;
        stsm4t(d, pack_bf16(o[0][0], o[0][1]), pack_bf16(o[0][2], o[0][3]), pack_bf16(o[1][0], o[1][1]), pack_bf16(o[1][2], o[1][3]));
        stsm4t(d + 1024, pack_bf16(o[2][0], o[2][1]), pack_bf16(o[2][2], o[2][3]), pack_bf16(o[3][0], o[3][1]), pack_bf16(o[3][2], o[3][3]));
    }
}
__device__ __forceinline__ void vs_attention(uint32_t sb, int h, int par, int up, int lane) {
    const uint32_t rec = sb + SM_AT + par * REC_BYTES, bar = sb + MB_AT + par * 8, out = sb + SM_AO0 + par * (SM_AO1 - SM_AO0);
    auto wait_step = [&](uint32_t v) { uint32_t n = 0; while (lds32(sb + SM_PH) < v) { spin_guard(++n); __nanosleep(ATT_NAP); } };
    const uint32_t epoch = *(volatile uint32_t*)&g_epoch;
    auto wait_record = [&](int g) {
        const uint32_t tag = epoch * NSEG + 1 + g;
        const uint32_t* p = lane == 0 ? g_flags[epoch & 1] + F_Q + (g >> 2) : g_fkt + h * 8 + (g == NSEG - 1 ? 2 : 0) + ((lane - 1) & 1);
        uint32_t n = 0;
        while (true) {
            const uint32_t x = ld_acquire(p);
            if (__all_sync(~0u, lane == 0 ? x >= 16 : (int)(x - tag) >= 0)) break;
            spin_guard(++n); __nanosleep(PUB_NAP);
        }
        fence_async();
    };
    auto request = [&](int g) {
        asm volatile("{.reg .pred p; elect.sync _|p, 0xffffffff;\n@p mbarrier.arrive.expect_tx.shared::cta.b64 _, [%2], %3;\n"
                     "@p cp.async.bulk.shared::cluster.global.mbarrier::complete_tx::bytes [%0], [%1], 4096, [%2];\n"
                     "@p cp.async.bulk.shared::cluster.global.mbarrier::complete_tx::bytes [%0 + 4096], [%1 + 8192], 4096, [%2];\n"
                     "@p cp.async.bulk.shared::cluster.global.mbarrier::complete_tx::bytes [%0 + 8192], [%4], 8192, [%2];}" :: "r"(rec), "l"(ox_ptr(h, g)), "r"(bar), "n"(REC_BYTES), "l"(kt_ptr(h, g)) : "memory");
        VT(g, 1);
    };
    auto announce = [&](int g) {
        bulk_wait_all(); fence_async(); fence_release();
        __syncwarp();
        red_add_if(g_flags[epoch & 1] + F_ATT + (g >> 1), 1, lane == 0);
        VT(g, 7);
    };
    bool next = false;
#pragma unroll 1
    for (int s = par; s < NSEG; s += 2) {
        const bool late = s < ATT_EAGER, late1 = s <= ATT_EAGER;
        if (!up && !next) {
            wait_record(s);
            if (late1) wait_step(2 * s + ATT_REQ);
            request(s);
        }
        if (late1) wait_step(2 * s + ATT_H1);
        mbar_wait(bar, (s >> 1) & 1);
        mbar_wait(sb + MB_KM + (s & 7) * 8, (s >> 3) & 1);
        VT(s, up ? 5 : 3);
        att_pass(rec, out + up * 2048 + lane * 16, sb + SM_VR + (s % NVR) * 8192 + lane * 16, sb + SM_KM + (s % NKM) * 4096 + lane * 8, up, lane, [&] {
            if (up) VT(s, 2);
            asm volatile("cp.async.bulk.wait_group.read 0;" ::: "memory");
            bar_sync(2 + par, 64);
            next = late && !up && lds32(sb + SM_PH) >= 2 * s + 4 + ATT_REQ;
            if (next) { wait_record(s + 2); request(s + 2); }
            if (late) wait_step(2 * s + ATT_H2);
        });
        fence_async_smem();
        bar_sync(par, 64);
        VT(s, up ? 6 : 4);
        if (up) {
            sts32_if(sb + SM_AD + par * 4, (s >> 1) + 1, lane == 0);
            if (s >= 2 && s < ATT_NOW + 2) announce(s - 2);
            if (s < ATT_NOW) wait_step(2 * s + ATT_FLAG);
            asm volatile("{.reg .pred p; elect.sync _|p, 0xffffffff;\n@p cp.async.bulk.global.shared::cta.bulk_group [%0], [%1], 4096;\n"
                         "@p cp.async.bulk.global.shared::cta.bulk_group [%0 + 8192], [%1 + 4096], 4096;\ncp.async.bulk.commit_group;}" :: "l"(ox_ptr(h, s)), "r"(out) : "memory");
            if (s >= ATT_NOW) announce(s);
            __syncwarp();
        }
    }
}

template <bool VS>
__device__ __forceinline__ void chain_aux(uint32_t sb, int cta, int h, int j, int w, int lane, const Maps* maps, const Ptrs* P) {
    if (w == 0) {
        if (lane == 0) {
            { const uint32_t c0 = clock(); while ((uint32_t)clock() - c0 < (uint32_t)START_DELAY) {} }
            if (PF_MODE) {
                const int c96 = cta_now();
#pragma unroll 1
                for (int i = 0; i < 27; i++) {
                    const int r = i * 96 + c96;
                    if (r < 2560) bulk_prefetch(reinterpret_cast<const unsigned char*>(r < 640 ? P->wo : r < 1280 ? P->wk : r < 1920 ? P->wv : P->wq) + (r % 640) * 8192, 8192);
                    if (PF_NAP) { const uint32_t c0 = clock(); while ((uint32_t)clock() - c0 < (uint32_t)PF_NAP) {} }
                }
            }
            if (!VS) {
                const int ec = h * DH + 64 * j;
#pragma unroll 1
                for (int n = -5; n < 8; n++) {
                    const int m = n - W_DEPTH;
                    if (m >= -5) mbar_wait(sb + (m < 0 ? MB_PO + (m + 5) * 8 : MB_PF + m * 8), 0);
                    if (n >= 5) mbar_wait(sb + MB_PE + (n == 7 ? 8 : 0), 0);
                    const uint32_t bar = sb + (n < 0 ? MB_PO + (n + 5) * 8 : MB_PF + n * 8);
                    mbar_arrive_tx(bar, n < 0 ? 16384 : 20480);
                    if (n < 0) tma2d(sb + STG_O + (n + 5) * 16384, &maps->o, 64 * (((j ? 0x87394 : 0x65210) >> (4 * n + 20)) & 15), h * DH, bar);
                    else tma2d(sb + STG_QK + (n % 5) * 20480, (n & 4) ? &maps->q : &maps->k, ec, 160 * (n & 3), bar);
                    if (n >= 2 && n < 5) tma2d_prefetch(&maps->q, ec, 160 * (n - 1));
                }
            } else {
#pragma unroll 1
                for (int n = 0; n < 8; n++) {
                    const int m = n - W_DEPTH_V, c = (n & 1) | (n & 2) << 1 | (n & 4) >> 1;
                    if (m >= 0) mbar_wait(sb + MB_PF + ((m & 1) | (m & 2) << 1 | (m & 4) >> 1) * 8, 0);
                    mbar_arrive_tx(sb + MB_PF + c * 8, 20480);
                    tma2d(sb + STG_V + c * 20480, &maps->v, h * DH + 64 * (c >> 2), 160 * (c & 3), sb + MB_PF + c * 8);
                }
            }
            if (VS) {
                wait_flag(launch_flags() + F_LN0, 128);
                fence_async();
                mbar_wait(sb + MB_L0 + 8, 0);
                mbar_arrive_tx(sb + MB_XN, 40960);
                tma3d(sb + SM_XN, &maps->xnp, 0, 0, 0, sb + MB_XN);
                mbar_wait(sb + MB_GO, 0);
                mbar_arrive_tx(sb + MB_XN2, 40960);
                tma3d(sb + SM_XN2, &maps->xnp, 0, 32, 0, sb + MB_XN2);
                mbar_wait(sb + MB_XNF, 0);
                mbar_arrive_tx(sb + MB_XN, 40960);
                tma3d(sb + SM_XN, &maps->xnp, 0, 64, 0, sb + MB_XN);
            }
        }
    }
    if (!VS && w == 0) {
        __syncwarp();
        mbar_arrive_tx_if(sb + MB_VX, 8192, lane == 0);
#pragma unroll 1
        for (int s = 0;; s++) {
            const uint32_t ph = s & 1;
            if (s < NSEG - 1) mbar_wait(sb + MB_VX, ph);
            mbar_arrive_tx_if(sb + MB_S + lane * 8, lane == 0 ? 1280 : lane == 1 ? 2048 : 8192, lane < (s < NSEG - 2 ? 3 : 2));
            bar_arrive(BAR_RED, 192);
            if (s == NSEG - 1) break;
            if (s) mbar_wait(sb + MB_MEM, ph ^ 1);
            EV(0, clk());
            wait_clk(clk(), SIG_POLL);
            const int lead = lead_time(h, stamp(s, -100000), lane);
            EV(1, clk()); EV(5, lead);
            sts32(sb + SM_USC + 4, lead << 6 | s);
            if (j == 0 && lane == 0) st_async32((sb ^ 2 * SM_RANK) + SM_RC + 8, lead, (sb ^ 2 * SM_RANK) + MB_R);
            __syncwarp();
            mbar_wait(sb + MB_PUB + ph * 8, (s >> 1) & 1);
            mbar_wait(sb + MB_S, ph); mbar_wait(sb + MB_V, ph);
        }
    } else if (!VS && w == 3) {
        wait_flag(launch_flags() + F_LN0, 128);
        mbar_wait(sb + MB_L0 + 8, 0);
        float usc = pow2i(-(int)lds32(sb + SM_CST));
        fence_async();
        tma_xn(sb + SM_XN, &maps->xnp, 0, sb + MB_XN);
        mbar_wait(sb + MB_XNF, 0);
        tma_xn(sb + SM_XN, &maps->xnp, 1, sb + MB_XN);
#pragma unroll 1
        for (int s = 0;; s++) {
            wait_count(sb + SM_CST + 44, max(s - 1, 0));
            if (s < NSEG - 1) {
                mbar_wait(sb + MB_XNF, (s & 1) ^ 1);
                if (s && XN_AT) mbar_wait(sb + MB_MEM, (s & 1) ^ 1);
                if (XN_NAP) wait_clk(clk(), XN_NAP);
                tma_xn(sb + SM_XN, &maps->xnp, min(s + 2, NSEG - 1), sb + MB_XN);
            }
            bar_sync(BAR_BGO, 288);
            if (s == NSEG - 1) break;
            if (s == 0) { mbar_wait(sb + MB_CST, 0); fence_async(); }
            usc = pow2i(-out_scale(sb, usc, lane));
            sts32(sb + SM_USC + lane * 8, __float_as_uint(usc));
            EV(6, clk());
            bar_sync(BAR_O, 288);
            sfence(P->zero);
            EV(4, clk());
            st_async64_if((sb ^ 2 * SM_RANK) + SM_RC, clk() + (POLL_EARLY - V_LEAD), __float_as_uint(usc), (sb ^ 2 * SM_RANK) + MB_R, j == 0 && lane == 0);
            mbar_wait(sb + MB_XN, s & 1);
            EV(7, clk());
            mbar_wait(sb + MB_KTF, (s & 1) ^ 1);
            bar_arrive(BAR_PW, 288);
        }
    } else if (w == 1) {
        if (lane == 0) {
            if (cta_now() < 16) { mbar_wait(sb + MB_L0, 0); __threadfence(); atomicAdd(launch_flags() + F_LN0, 8); }
            mbar_wait(sb + MB_L0 + 8, 0); __threadfence(); atomicAdd(launch_flags() + F_LN, 8);
            const uint32_t tag0 = launch_tag();
#pragma unroll 1
            for (int s = 0; s < (VS ? 0 : NSEG); s++) {
                mbar_wait(sb + MB_KT, s & 1);
                fence_async_smem();
                bulk_s2g(kt_ptr(h, s) + j * 4096, sb + ((s & 1) ? SM_KT1 : SM_KT0), 4096);
                asm volatile("cp.async.bulk.wait_group.read 0;" ::: "memory");
                mbar_arrive(sb + MB_KTF);
                bulk_wait_all();
                if (s < NSEG - 1) { sts32(sb + SM_CST + 40, s + 1); continue; }
                fence_async(); __threadfence();
                st_relaxed32(g_fkt + h * 8 + 2 + j, tag0 + s);
            }
        }
    } else if (w == 2) {
        unsigned char* z = g_ring + ring_pos(cta) + lane * 16;
        uint32_t* fl = launch_flags();
        if (!VS && lane < 16) st_relaxed128(z + 32768, make_uint4(0, 0, 0, 0));
        __syncwarp();
        if (lane == 0) {
            mbar_wait(sb + MB_OM, 0);
            if (TRIG == 2) asm volatile("griddepcontrol.launch_dependents;");
            __threadfence();
            flag_add(fl + F_INIT);
            wait_flag(fl + F_INIT, LN_CTAS);
            const float wv = __uint_as_float(ld_relaxed32(fl + F_WV)), wo = __uint_as_float(ld_relaxed32(fl + F_WO));
            sts64(sb + SM_CST + 32, __float_as_uint(wv * wo * (1.02f * 4096.0f * 25.3f)), ld_relaxed32(fl + F_XN));
            if (VS) fence_async();
            mbar_arrive(sb + MB_CST);
        }
        __syncwarp();
        if (!VS) {
            const uint32_t tag0 = launch_tag();
#pragma unroll 1
            for (int s = 0; s < NSEG; s++) {
                mbar_wait(sb + MB_PUB + (s & 1) * 8, (s >> 1) & 1);
                if (lane == 0 && s == 0) GT(1);
                if (lane == 0 && s == NSEG - 1) GT(2);
                if (s < NSEG - 1 && PUB_LATE) mbar_wait(sb + MB_MEM, s & 1);
                const int zs = (s + 3) & 3;
                if (lane < 16 && s < NSEG - 1) st_relaxed128(z + (zs & 1) * 512 + (zs >> 1) * 32768, make_uint4(0, 0, 0, 0));
                if (s == NSEG - 1) break;
                { uint32_t n = 0; while (lds32(sb + SM_CST + 40) <= (uint32_t)min(s + K_AHEAD, NSEG - 2)) { spin_guard(++n); __nanosleep(K_NAP); } }
                fence_async();
                fence_release();
                __syncwarp();
                if (lane == 0) {
                    st_relaxed32(g_fkt + h * 8 + j, tag0 + min(s + K_AHEAD, NSEG - 2));
                    asm volatile("st.release.cta.shared.u32 [%0], %1;" :: "r"(sb + SM_CST + 44), "r"(s + 1) : "memory");
                }
            }
        }
    }
    if (VS) { __syncwarp(); const int ww = __reduce_max_sync(~0u, w); vs_attention(sb, h, ww & 1, ww >> 1, lane); }
}

constexpr int NG = 36;
constexpr int GS_Q = 49152;
constexpr int GS_OA = 163840;
constexpr int GB_QF = SM_BAR, GB_QE = SM_BAR + 32, GB_OF = SM_PROF, GB_OE = SM_PROF + 64, GB_WO = SM_BAR + 128, GB_QD = SM_BAR + 136;
constexpr int G_SEL = SM_CST, G_RS = SM_BAR + 160;
constexpr int G_Q = SM_BAR + 256, GB_ML = SM_BAR + 144;
constexpr int BAR_G = 1, BAR_W = 2;

__device__ __forceinline__ uint4 ldcg128(const void* p) { uint4 v; asm volatile("ld.global.cg.v4.u32 {%0,%1,%2,%3}, [%4];" : "=r"(v.x), "=r"(v.y), "=r"(v.z), "=r"(v.w) : "l"(p)); return v; }
__device__ __forceinline__ uint2 ldcg64(const void* p) { uint2 v; asm volatile("ld.global.cg.v2.u32 {%0,%1}, [%2];" : "=r"(v.x), "=r"(v.y) : "l"(p)); return v; }
__device__ __forceinline__ uint4 ld128(const void* p) { uint4 v; asm volatile("ld.global.v4.u32 {%0,%1,%2,%3}, [%4];" : "=r"(v.x), "=r"(v.y), "=r"(v.z), "=r"(v.w) : "l"(p) : "memory"); return v; }
__device__ __forceinline__ uint2 ld64(const void* p) { uint2 v; asm volatile("ld.global.v2.u32 {%0,%1}, [%2];" : "=r"(v.x), "=r"(v.y) : "l"(p) : "memory"); return v; }
__device__ __forceinline__ float bflo(uint32_t w) { return __uint_as_float(w << 16); }
__device__ __forceinline__ float bfhi(uint32_t w) { return __uint_as_float(w & 0xffff0000u); }
__device__ __forceinline__ float sigmoidf_(float x) { return __fdividef(1.0f, 1.0f + __expf(-x)); }
#define R8(c, i) "+f"(c[i]), "+f"(c[i + 1]), "+f"(c[i + 2]), "+f"(c[i + 3]), "+f"(c[i + 4]), "+f"(c[i + 5]), "+f"(c[i + 6]), "+f"(c[i + 7])
__device__ __forceinline__ void wgmma_n256(float (&c)[128], uint64_t a, uint64_t b, uint32_t acc) {
    asm volatile("{.reg .pred p; setp.ne.u32 p, %130, 0;\n"
        "wgmma.mma_async.sync.aligned.m64n256k16.f32.bf16.bf16 {%0,%1,%2,%3,%4,%5,%6,%7,%8,%9,%10,%11,%12,%13,%14,%15,%16,%17,%18,%19,%20,%21,%22,%23,%24,%25,%26,%27,%28,%29,%30,%31,"
        "%32,%33,%34,%35,%36,%37,%38,%39,%40,%41,%42,%43,%44,%45,%46,%47,%48,%49,%50,%51,%52,%53,%54,%55,%56,%57,%58,%59,%60,%61,%62,%63,"
        "%64,%65,%66,%67,%68,%69,%70,%71,%72,%73,%74,%75,%76,%77,%78,%79,%80,%81,%82,%83,%84,%85,%86,%87,%88,%89,%90,%91,%92,%93,%94,%95,"
        "%96,%97,%98,%99,%100,%101,%102,%103,%104,%105,%106,%107,%108,%109,%110,%111,%112,%113,%114,%115,%116,%117,%118,%119,%120,%121,%122,%123,%124,%125,%126,%127},%128,%129,p,1,1,0,1;}"
        : R8(c, 0), R8(c, 8), R8(c, 16), R8(c, 24), R8(c, 32), R8(c, 40), R8(c, 48), R8(c, 56), R8(c, 64), R8(c, 72), R8(c, 80), R8(c, 88), R8(c, 96), R8(c, 104), R8(c, 112), R8(c, 120)
        : "l"(a), "l"(b), "r"(acc));
}
__device__ __forceinline__ void wgmma_n128(float (&c)[64], uint64_t a, uint64_t b, uint32_t acc) {
    asm volatile("{.reg .pred p; setp.ne.u32 p, %66, 0;\n"
        "wgmma.mma_async.sync.aligned.m64n128k16.f32.bf16.bf16 {%0,%1,%2,%3,%4,%5,%6,%7,%8,%9,%10,%11,%12,%13,%14,%15,%16,%17,%18,%19,%20,%21,%22,%23,%24,%25,%26,%27,%28,%29,%30,%31,"
        "%32,%33,%34,%35,%36,%37,%38,%39,%40,%41,%42,%43,%44,%45,%46,%47,%48,%49,%50,%51,%52,%53,%54,%55,%56,%57,%58,%59,%60,%61,%62,%63},%64,%65,p,1,1,0,1;}"
        : R8(c, 0), R8(c, 8), R8(c, 16), R8(c, 24), R8(c, 32), R8(c, 40), R8(c, 48), R8(c, 56)
        : "l"(a), "l"(b), "r"(acc));
}
constexpr int GB_DONE = SM_PROF + 512, GD_MLP = 8, GD_O = 9;
__device__ __forceinline__ void task_done(uint32_t sb, int i, bool first) { __syncwarp(); mbar_arrive_if(sb + GB_DONE + i * 8, first); }
__device__ __forceinline__ void gemm_publisher(uint32_t sb, int c, int lane) {
    uint32_t* fl = launch_flags();
#pragma unroll 1
    for (int i = 0; i < GD_O + 32; i++) {
        if (i < GD_MLP ? c + NG * i >= 256 : i == GD_MLP ? c < NG - 27 : c == 3) continue;
        uint32_t n = 0;
        while (!mbar_try_wait(sb + GB_DONE + i * 8, 0)) { spin_guard(++n); if (P_NAP) __nanosleep(P_NAP); }
        fence_release();
        red_add_if(fl + (i < GD_MLP ? F_Q + ((c + NG * i) >> 4) : i == GD_MLP ? F_MOD : F_O - GD_O + i), 1, lane == 0);
    }
}

__device__ __forceinline__ float warp_sum(float v) {
#pragma unroll
    for (int o = 16; o; o >>= 1) v += __shfl_xor_sync(~0u, v, o);
    return v;
}
__device__ __forceinline__ void g_select(uint32_t tmp, uint32_t sb, int tid) {
    const int lane = tid & 31, warp = tid >> 5;
    uint32_t key[8];
#pragma unroll
    for (int i = 0; i < 8; i++) {
        const int tok = tid + 256 * i;
        const uint32_t b = __float_as_uint(__ldcg(g_r + tok) + 0.0f) >> 16;
        key[i] = (((b & 0x8000u) ? (~b & 0xffffu) : (b | 0x8000u)) << 16) | (uint32_t)(S_TOK - 1 - tok);
    }
    auto pick = [&](uint32_t* k, int n, uint32_t dst) {
        for (int c = 0; c < 8; c++) {
            uint32_t m = 0;
#pragma unroll
            for (int i = 0; i < 8; i++) if (i < n) m = max(m, k[i]);
            m = __reduce_max_sync(~0u, m);
#pragma unroll
            for (int i = 0; i < 8; i++) if (i < n && k[i] == m) k[i] = 0;
            if (lane == 0) sts32(dst + c * 4, m);
        }
    };
    pick(key, 8, tmp + warp * 32);
    bar_sync(BAR_G, 256);
    if (warp == 0) {
        const uint2 x = lds64(tmp + lane * 8);
        key[0] = x.x; key[1] = x.y;
        pick(key, 2, sb + G_SEL);
        __syncwarp();
        if (lane < 8) {
            const int tok = S_TOK - 1 - (int)(lds64(sb + G_SEL + (lane & ~1) * 4).x * (1 - (lane & 1)) + lds64(sb + G_SEL + (lane & ~1) * 4).y * (lane & 1) & 0xffffu);
            __syncwarp(0xff);
            sts32(sb + G_SEL + lane * 4, tok);
            sts32(sb + G_RS + lane * 4, __float_as_uint(bf16_round(sigmoidf_(__ldcg(g_r + tok)))));
        }
    }
    bar_sync(BAR_G, 256);
}

__device__ __forceinline__ void g_mlp(uint32_t sb, int part, int tid) {
    const int warp = tid >> 5, lane = tid & 31, m = lane >> 3, sg = lane & 7, r = lane >> 2, jj = lane & 3;
    const uint32_t xs = sb + 163840, hs = xs + 10240, gs = hs + 1024;
    const uint32_t tok = lds64(sb + G_SEL + (r & ~1) * 4 ).x * (1 - (r & 1)) + lds64(sb + G_SEL + (r & ~1) * 4).y * (r & 1);
#pragma unroll 1
    for (int k = warp; k < 40; k += 8) {
        const uint32_t* p = reinterpret_cast<const uint32_t*>(g_xn + tok * DM + 16 * k + 2 * jj);
        sts64(xs + k * 256 + lane * 8, __ldcg(p), __ldcg(p + 4));
    }
    bar_sync(BAR_G, 256);
    mbar_wait(sb + GB_ML, 0);
    float a[4] = {0, 0, 0, 0};
    {
        const uint32_t base = sb + (warp >> 2) * 81920 + (8 * (m >> 1) + sg) * 128 + (((2 * (warp & 3) + (m & 1)) ^ sg) << 4);
#pragma unroll 4
        for (int k = 0; k < 40; k++) { const uint2 b = lds64(xs + k * 256 + lane * 8); mma16816(a, ldsm4t(base + k * 2048), b.x, b.y); }
    }
    if (warp < 4) {
#pragma unroll
        for (int i = 0; i < 4; i++) { const float g = bf16_round(a[i]); a[i] = bf16_round(g * sigmoidf_(g)); }
        sts128f(gs + tid * 16, a[0], a[1], a[2], a[3]);
    }
    bar_sync(BAR_G, 256);
    if (tid == 0) mbar_arrive(sb + GB_QD);
    if (warp >= 4) {
        const uint4 g = lds128(gs + (tid - 128) * 16);
        sts64(hs + (warp - 4) * 256 + lane * 8, movmat(pack_bf16(__uint_as_float(g.x) * bf16_round(a[0]), __uint_as_float(g.y) * bf16_round(a[1]))),
              movmat(pack_bf16(__uint_as_float(g.z) * bf16_round(a[2]), __uint_as_float(g.w) * bf16_round(a[3]))));
    }
    bar_sync(BAR_G, 256);
    mbar_wait(sb + GB_ML, 1);
#pragma unroll 1
    for (int tile = warp; tile < 40; tile += 8) {
        const uint32_t base = sb + (tile >> 2) * 8192 + (8 * (m >> 1) + sg) * 128 + (((2 * (tile & 3) + (m & 1)) ^ sg) << 4);
        float y[4] = {0, 0, 0, 0};
#pragma unroll
        for (int k = 0; k < 4; k++) { const uint2 b = lds64(hs + k * 256 + lane * 8); mma16816(y, ldsm4t(base + k * 2048), b.x, b.y); }
        float* dst = g_y + (part * 8 + 2 * jj) * DM + 16 * tile + r;
        dst[0] = y[0]; dst[DM] = y[1]; dst[8] = y[2]; dst[DM + 8] = y[3];
    }
}

__device__ __forceinline__ void quad_transpose(uint32_t (&w)[4], int lane) {
    const bool o1 = lane & 1, o2 = lane & 2;
    uint32_t a = __shfl_xor_sync(~0u, o1 ? w[0] : w[1], 1), b = __shfl_xor_sync(~0u, o1 ? w[2] : w[3], 1);
    if (o1) { w[0] = a; w[2] = b; } else { w[1] = a; w[3] = b; }
    a = __shfl_xor_sync(~0u, o2 ? w[0] : w[2], 2); b = __shfl_xor_sync(~0u, o2 ? w[1] : w[3], 2);
    if (o2) { w[0] = a; w[1] = b; } else { w[2] = a; w[3] = b; }
}
__device__ __forceinline__ void g_epilogue(const Ptrs& P, uint32_t sb, int u, int tile, int lane) {
    const uint4* part = g_part + (u % 6) * (7 * 64 * DM / 8) + tile * 64 + lane;
    const uint32_t tok = u * 64 + ((tile >> 2) & 3) * 16 + (lane >> 2), col = (tile >> 4) * 128 + (tile & 3) * 32 + (lane & 3) * 8;
    uint4 p[7][2], xw[2], nw[2];
#pragma unroll
    for (int k = 0; k < 7; k++)
#pragma unroll
        for (int g = 0; g < 2; g++) p[k][g] = ld128(part + k * (64 * DM / 8) + g * 32);
#pragma unroll
    for (int u = 0; u < 2; u++) { xw[u] = ld128(P.x + (tok + 8 * u) * DM + col); nw[u] = ld128(g_xn + (tok + 8 * u) * DM + col); }
    const uint4 s0 = lds128(sb + G_SEL), s1 = lds128(sb + G_SEL + 16);
    uint32_t sw[2][4];
#pragma unroll
    for (int g = 0; g < 4; g++) {
        float v[4] = {0, 0, 0, 0};
#pragma unroll
        for (int k = 0; k < 7; k++) {
            const uint32_t a = (g & 1) ? p[k][g >> 1].z : p[k][g >> 1].x, b = (g & 1) ? p[k][g >> 1].w : p[k][g >> 1].y;
            v[0] += bflo(a); v[1] += bfhi(a); v[2] += bflo(b); v[3] += bfhi(b);
        }
        sw[0][g] = pack_bf16(v[0], v[1]); sw[1][g] = pack_bf16(v[2], v[3]);
    }
#pragma unroll
    for (int u = 0; u < 2; u++) {
        quad_transpose(sw[u], lane);
        const uint32_t t = tok + 8 * u;
        uint32_t gw[4] = {nw[u].x, nw[u].y, nw[u].z, nw[u].w};
        const uint32_t xx[4] = {xw[u].x, xw[u].y, xw[u].z, xw[u].w};
        const int k = s0.x == t ? 0 : s0.y == t ? 1 : s0.z == t ? 2 : s0.w == t ? 3 : s1.x == t ? 4 : s1.y == t ? 5 : s1.z == t ? 6 : s1.w == t ? 7 : -1;
        if (k >= 0) {
            const uint4 y0 = ld128(g_yf + k * DM + col), y1 = ld128(g_yf + k * DM + col + 4);
            gw[0] = pack_bf16(bflo(gw[0]) + __uint_as_float(y0.x), bfhi(gw[0]) + __uint_as_float(y0.y));
            gw[1] = pack_bf16(bflo(gw[1]) + __uint_as_float(y0.z), bfhi(gw[1]) + __uint_as_float(y0.w));
            gw[2] = pack_bf16(bflo(gw[2]) + __uint_as_float(y1.x), bfhi(gw[2]) + __uint_as_float(y1.y));
            gw[3] = pack_bf16(bflo(gw[3]) + __uint_as_float(y1.z), bfhi(gw[3]) + __uint_as_float(y1.w));
        }
        uint32_t o[4];
#pragma unroll
        for (int i = 0; i < 4; i++) {
            const uint32_t gt = pack_bf16(bflo(gw[i]) * sigmoidf_(bflo(gw[i])), bfhi(gw[i]) * sigmoidf_(bfhi(gw[i])));
            const uint32_t pr = pack_bf16(bflo(sw[u][i]) * bflo(gt), bfhi(sw[u][i]) * bfhi(gt));
            o[i] = pack_bf16(bflo(xx[i]) + bflo(pr), bfhi(xx[i]) + bfhi(pr));
        }
        *reinterpret_cast<uint4*>(P.out + t * DM + col) = make_uint4(o[0], o[1], o[2], o[3]);
    }
}

__device__ __forceinline__ void stg128_if(void* p, const uint4& v, bool c) {
    asm volatile("{.reg .pred p; setp.ne.u32 p, %5, 0; @p st.global.v4.u32 [%0], {%1, %2, %3, %4};}" :: "l"(p), "r"(v.x), "r"(v.y), "r"(v.z), "r"(v.w), "r"((uint32_t)c) : "memory");
}
struct OSlice {
    int nt, ks, nkb, kb0; bool on;
    __device__ __forceinline__ OSlice(int c) { const int o = c < 4 ? c + 32 : c - 4; ks = o / 5; nt = o - 5 * ks; on = o < 35; nkb = ks ? 9 : 10; kb0 = ks ? 1 + 9 * ks : 0; }
};
__device__ __forceinline__ bool wg_all(int id, bool x) {
    uint32_t r;
    asm volatile("{.reg .pred p, q; setp.ne.u32 p, %2, 0; barrier.red.and.pred q, %1, 128, p; selp.u32 %0, 1, 0, q;}" : "=r"(r) : "r"(id), "r"((uint32_t)x) : "memory");
    return r;
}
template <int wg>
__device__ __forceinline__ void gemm_tail(const Ptrs& P, uint32_t sb, int c, int tid) {
    const int warp = tid >> 5, lane = tid & 31;
    const uint32_t* fl = launch_flags();
    if (wg == 0) {
        const OSlice os(c);
        if (!os.on) return;
        wg_fence(); wg_commit(); wg_fence(); wg_commit(); wg_wait<0>();
        const bool ten = __reduce_max_sync(~0u, os.nkb) == 10, first = lane == 0;
        uint4* const part = g_part + os.ks * (64 * DM / 8) + (os.nt * 4 + warp) * 256 + lane;
        mbar_wait(sb + GB_WO, 0);
        uint32_t it = 0, ne = 80, slot = 0;
        bool pending = false;
        uint4 pw[8] = {};
        uint4* dst = part;
        uint32_t i0 = 0, full = 0;
#pragma unroll 1
        for (int u = 0; u < 32; u++) {
            float acc[64];
            const uint64_t b0 = P.desc_b + (i0 & P.zero);
#pragma unroll
            for (int i = 0; i < 10; i++) {
                if (i == 9 && !ten) break;
                const uint32_t st = (i0 + i) & 7;
                if (!full) mbar_wait(sb + GB_OF + st * 8, ((i0 + i) >> 3) & 1);
                const uint64_t alo = P.desc_oa + ((SM_BASE + GS_OA) >> 4) + st * 512, blo = b0 + ((SM_BASE + i * 16384) >> 4);
                wg_fence();
#pragma unroll
                for (int k = 0; k < 4; k++) {
                    wgmma_n128(acc, alo + k * 16, blo + k * 128, i | k);
                    if (k == 0) full = mbar_try(sb + GB_OF + ((i0 + i + 1) & 7) * 8, ((i0 + i + 1) >> 3) & 1);
                }
                wg_commit();
                if (i < 8) stg128_if(dst + i * 32, pw[i], pending);
                if (i == 7) task_done(sb, GD_O + u - 1, first && pending);
                if (i == 5) ne = ld_relaxed32(fl + F_EPI + max(u - 6, 0));
                if (i > 1) { wg_wait<2>(); mbar_arrive_if(sb + GB_OE + ((i0 + i + 6) & 7) * 8, first); }
            }
            it += os.nkb;
            i0 = __reduce_max_sync(~0u, it);
            dst = part + slot * (7 * 64 * DM / 8);
            slot = slot == 5 ? 0 : slot + 1;
            pending = wg_all(BAR_W, u < 31 && (u < 6 || ne >= 80) && full);
            wg_wait<0>();
            mbar_arrive_if(sb + GB_OE + ((it + 6 + (lane & 1)) & 7) * 8, lane < 2);
#pragma unroll
            for (int g = 0; g < 8; g++) pw[g] = make_uint4(pack_bf16(acc[8 * g], acc[8 * g + 1]), pack_bf16(acc[8 * g + 2], acc[8 * g + 3]), pack_bf16(acc[8 * g + 4], acc[8 * g + 5]), pack_bf16(acc[8 * g + 6], acc[8 * g + 7]));
            if (!pending) {
                if (u >= 6 && __any_sync(~0u, ne < 80)) { uint32_t n = 0; while (__any_sync(~0u, ld_relaxed32(fl + F_EPI + u - 6) < 80)) { spin_guard(++n); __nanosleep(100); } }
#pragma unroll
                for (int g = 0; g < 8; g++) dst[g * 32] = pw[g];
                task_done(sb, GD_O + u, first);
            }
        }
    } else {
        if (c < 20) {
            if (tid == 128) wait_flag(fl + F_MOD, 27);
            bar_sync(BAR_W + 1, 128);
            if (tid < 192) {
                const int i = c * 64 + tid - 128;
                float y[4] = {0, 0, 0, 0};
#pragma unroll
                for (int q = 0; q < 27; q++) {
                    const uint4 w = ldcg128(g_y + q * (8 * DM) + i * 4);
                    y[0] += __uint_as_float(w.x); y[1] += __uint_as_float(w.y); y[2] += __uint_as_float(w.z); y[3] += __uint_as_float(w.w);
                }
                const uint2 rw = lds64(sb + G_RS + ((i / 160) & ~1) * 4);
                const float rs = __uint_as_float(((i / 160) & 1) ? rw.y : rw.x);
                *reinterpret_cast<float4*>(g_yf + i * 4) = make_float4(bf16_round(bf16_round(y[0]) * rs), bf16_round(bf16_round(y[1]) * rs), bf16_round(bf16_round(y[2]) * rs), bf16_round(bf16_round(y[3]) * rs));
            }
            bar_sync(BAR_W + 1, 128);
            if (tid == 128) flag_add(const_cast<uint32_t*>(fl) + F_YF);
        }
        { uint32_t n = 0; while (__any_sync(~0u, ld_acquire(fl + F_YF) < 20)) { spin_guard(++n); __nanosleep(E_NAP); } }
#pragma unroll 1
        for (int g = (warp & 3) * NG + c; g < 32 * 80; g += 4 * NG) {
            const int u = g / 80;
            { uint32_t n = 0; while (__any_sync(~0u, ld_acquire(fl + F_O + u) < 35)) { spin_guard(++n); __nanosleep(u < 30 ? E_NAP : G_NAP); } }
            g_epilogue(P, sb, u, g - 80 * u, lane);
            __syncwarp();
            red_add_if(const_cast<uint32_t*>(fl) + F_EPI + u, 1, lane == 0);
        }
    }
}

template <int N> struct Int { static constexpr int value = N; };
__device__ __forceinline__ void gemm_main(unsigned char* smem, uint32_t sb, int c, int tid, const Ptrs& P) {
    const int warp = tid >> 5, lane = tid & 31, wg = __reduce_max_sync(~0u, tid >> 7);
    uint32_t* fl = launch_flags();
    if (c == 0) for (int i = tid; i < F_WORDS; i += 256) g_flags[(*(volatile uint32_t*)&g_epoch & 1) ^ 1][i] = 0;
    bar_sync(BAR_G, 256);
    if (tid == 0) { if (LN_CTAS > 96) { __threadfence(); flag_add(fl + F_INIT); } wait_flag(fl + F_LN, LN_WARPS); GT(1); }
    bar_sync(BAR_G, 256);
    if (tid == 0) mbar_arrive(sb + GB_QD);
    if (tid == 0) GT(2);
    {
        float acc[128];
        uint32_t it = 0, pw[64];
        auto store = [&](int task, auto part) {
            constexpr int T0 = 4 * decltype(part)::value;
            uint4* dst = reinterpret_cast<uint4*>(ox_ptr(2 * (task & 15) + (T0 >> 3), 4 * (task >> 4) + (warp >> 1)) + (warp & 1) * 2048) + lane;
#pragma unroll
            for (int T = T0; T < T0 + 4; T++) dst[(T & 7) * 32] = make_uint4(pw[4 * T], pw[4 * T + 1], pw[4 * T + 2], pw[4 * T + 3]);
            if (T0 == 12) task_done(sb, task / NG, lane == 0);
        };
#pragma unroll 1
        for (int task = c;; task += NG) {
#pragma unroll 1
            for (int kb = 0; kb < 10; kb++, it++) {
                const uint32_t st = it & 3;
                mbar_wait(sb + GB_QF + st * 8, (it >> 2) & 1);
                const uint32_t stu = __reduce_max_sync(~0u, st);
                const uint64_t alo = P.desc + ((SM_BASE + stu * GS_Q + wg * 8192) >> 4), blo = P.desc_b + ((SM_BASE + stu * GS_Q + 16384) >> 4);
                wg_fence();
#pragma unroll
                for (int k = 0; k < 4; k++) wgmma_n256(acc, alo + k * 2, blo + k * 128, kb | k);
                wg_commit();
                if (kb > 0) { wg_wait<1>(); mbar_arrive_if(sb + GB_QE + ((it - 1) & 3) * 8, lane == 0); }
                if (task >= 2 * NG) {
                    if (kb == 0) store(task - NG, Int<0>()); else if (kb == 1) store(task - NG, Int<1>());
                    else if (kb == 2) store(task - NG, Int<2>()); else if (kb == 3) store(task - NG, Int<3>());
                }
            }
            wg_wait<0>();
            mbar_arrive_if(sb + GB_QE + ((it - 1) & 3) * 8, lane == 0);
#pragma unroll
            for (int i = 0; i < 64; i++) pw[i] = pack_bf16(acc[2 * i], acc[2 * i + 1]);
            if (task + NG >= 256) {
                bar_sync(BAR_G, 256);
                if (tid == 0) mbar_arrive(sb + GB_QD);
            }
            if (task < NG || task + NG >= 256) { store(task, Int<0>()); store(task, Int<1>()); store(task, Int<2>()); store(task, Int<3>()); }
            if (task + NG >= 256) break;
        }
    }
    g_select(sb + SM_PROF + 256, sb, tid);
    if (c >= NG - 27) {
        g_mlp(sb, c - (NG - 27), tid);
        task_done(sb, GD_MLP, lane == 0);
        bar_sync(BAR_G, 256);
        if (tid == 0) mbar_arrive(sb + GB_QD);
    }
    if (tid == 0) GT(3);
    if (wg == 0) gemm_tail<0>(P, sb, c, tid); else gemm_tail<1>(P, sb, c, tid);
    bar_sync(BAR_G, 256);
    if (tid == 128) GT(6);
    if (c == 0 && tid == 128) g_epoch = *(volatile uint32_t*)&g_epoch + 1;
}

__device__ __forceinline__ void gemm_producer_q(uint32_t sb, int c, int me, int lane, const Maps* maps) {
    const OSlice os(c);
    mbar_wait(sb + GB_QD, 0);
    fence_async();
    int task = c, kb = me;
#pragma unroll 1
    for (uint32_t it = me; task < 256; it += 3) {
        const uint32_t st = it & 3, bar = sb + GB_QF + st * 8, dst = sb + st * GS_Q;
        if (it >= Q_DEPTH) mbar_wait(sb + GB_QE + ((it - Q_DEPTH) & 3) * 8, ((it - Q_DEPTH) >> 2) & 1);
        asm volatile("{.reg .pred p; elect.sync _|p, 0xffffffff;\n@p mbarrier.arrive.expect_tx.shared::cta.b64 _, [%0], %8;\n"
                     "@p cp.async.bulk.tensor.2d.shared::cluster.global.mbarrier::complete_tx::bytes [%1], [%2, {%3, %4}], [%0];\n"
                     "@p cp.async.bulk.tensor.3d.shared::cluster.global.mbarrier::complete_tx::bytes [%5], [%6, {0, %3, %7}], [%0];}"
                     :: "r"(bar), "r"(dst), "l"(&maps->xn), "r"(64 * kb), "r"(128 * (task >> 4)), "r"(dst + 16384), "l"(&maps->q64), "r"(4 * (task & 15)), "n"(GS_Q) : "memory");
        const int pf = (int)it - PF_FROM;
        if (lane == 0) {
            if (pf >= 0 && pf < 18 && c >= NG - 27) {
                if (pf < 8) tma2d_prefetch(pf < 4 ? &maps->wg : &maps->wu, (c - (NG - 27)) * 64, 160 * (pf & 3));
                else tma2d_prefetch(&maps->wd, 64 * (pf - 8), (c - (NG - 27)) * 64);
            }
            if (pf >= 10 && pf < 10 + 2 * os.nkb && os.on) tma2d_prefetch(&maps->o64, 128 * os.nt + 64 * (pf & 1), 64 * (os.kb0 + ((pf - 10) >> 1)));
        }
        __syncwarp();
        kb += 3;
        if (kb >= 10) { kb -= 10; task += NG; }
    }
}
__device__ __forceinline__ void gemm_producer(uint32_t sb, int c, const Maps* maps) {
    const OSlice os(c);
    const int nt = os.nt, nkb = os.nkb, kb0 = os.kb0;
    mbar_wait(sb + GB_QD, 1);
    if (c >= NG - 27) {
        const int f0 = (c - (NG - 27)) * 64;
        mbar_arrive_tx(sb + GB_ML, 163840);
#pragma unroll 1
        for (int i = 0; i < 8; i++) { tma2d(sb + i * 20480, i < 4 ? &maps->wg : &maps->wu, f0, 160 * (i & 3), sb + GB_ML); wait_clk(clk(), G_PACE * 5 / 2); }
        mbar_wait(sb + GB_QD, 0);
        mbar_arrive_tx(sb + GB_ML, 81920);
#pragma unroll 1
        for (int i = 0; i < 10; i++) { tma2d(sb + i * 8192, &maps->wd, 64 * i, f0, sb + GB_ML); wait_clk(clk(), G_PACE); }
        mbar_wait(sb + GB_QD, 1);
    }
    if (!os.on) return;
    mbar_arrive_tx(sb + GB_WO, nkb * 16384);
#pragma unroll 1
    for (int i = 0; i < 2 * nkb; i++) { tma2d(sb + i * 8192, &maps->o64, 128 * nt + 64 * (i & 1), 64 * (kb0 + (i >> 1)), sb + GB_WO); wait_clk(clk(), G_PACE); }
}
__device__ __forceinline__ void gemm_producer_o(uint32_t sb, int c, int me, int lane, const __nv_bfloat16* x) {
    const uint32_t* fl = launch_flags() + F_ATT + lane;
    const OSlice os(c);
    const int nst = os.on ? os.nkb : 0;
    const uint32_t* src = g_ox + os.kb0 * 2048;
    if (os.on) mbar_wait(sb + GB_WO, 0);
    int known = 0, i = me;
    uint32_t it = me;
#pragma unroll 1
    for (int u = 0; u < 32; u++) {
        if (u >= known) {
            uint32_t n = 0;
            while ((known = __clz(__brev(~__ballot_sync(~0u, ld_acquire(fl) >= 64)))) <= u) { spin_guard(++n); __nanosleep(G_NAP); }
            fence_async();
        }
#pragma unroll 1
        for (; i < nst; i += 3, it += 3) {
            const uint32_t st = it & 7, bar = sb + GB_OF + st * 8;
            if (it >= O_DEPTH) mbar_wait(sb + GB_OE + ((it - O_DEPTH) & 7) * 8, ((it - O_DEPTH) >> 3) & 1);
            asm volatile("{.reg .pred p; elect.sync _|p, 0xffffffff;\n@p mbarrier.arrive.expect_tx.shared::cta.b64 _, [%2], 8192;\n"
                         "@p cp.async.bulk.shared::cluster.global.mbarrier::complete_tx::bytes [%0], [%1], 8192, [%2];}" :: "r"(sb + GS_OA + st * 8192), "l"(src + (u * 64 + i) * 2048), "r"(bar) : "memory");
        }
        i -= nst;
        if (me < 2 && lane == 0) bulk_prefetch((me ? x : g_xn) + u * (64 * DM) + min(c * 1144, 64 * DM - 1144), 2288);
        __syncwarp();
    }
}

__device__ __forceinline__ void stg64_if(const void* p, uint32_t x, uint32_t y, bool c) {
    asm volatile("{.reg .pred p; setp.ne.u32 p, %3, 0; @p st.global.v2.u32 [%0], {%1, %2};}" :: "l"(p), "r"(x), "r"(y), "r"((uint32_t)c) : "memory");
}
__device__ __forceinline__ void layernorm_rows(const Ptrs& P, uint32_t sb, int gw, int lane) {
    const int warp = gw & 7, nrow = gw + 2 * LN_WARPS < S_TOK ? 3 : gw + LN_WARPS < S_TOK ? 2 : 1;
    const uint32_t rows = sb + SM_XN + warp * (4 * 1280), bar = sb + MB_LN + warp * 8;
    if (lane == 0) mbar_arrive_tx(bar, (nrow + 1) * 1280);
    __syncwarp();
    if (lane <= nrow) bulk_g2s(rows + lane * 1280, lane ? P.x + (gw + (lane - 1) * LN_WARPS) * DM : P.wr, 1280, bar);
    sts32(sb + SM_CST + warp * 4, mem0_exp(P.mem0, lane));
    uint32_t* fl = launch_flags();
    const bool up = lane & 2;
    int slot[5];
#pragma unroll
    for (int i = 0; i < 5; i++) {
        const int t16 = (lane >> 2) + 8 * i, al = lane & 1, kh = t16 >= 20, tt = t16 - 20 * kh, ii = tt & 3, tau = tt >> 2;
        const int u = tau < 4 ? 2 * ii + al : 8 + al, w4 = tau < 4 ? tau : ii;
        slot[i] = (int)opaque(320 * kh + 16 * (2 * u + (w4 >> 1)) + 8 * (w4 & 1) + (up ? 4 : 0));
    }
    float nmax = 0;
#pragma unroll 1
    for (int n = (int)opaque(LN_WARM ? -1 : 0); n < nrow; n++) {
        if (n == 0) mbar_wait(bar, 0);
        const bool real = n >= 0;
        const int tok = gw + n * LN_WARPS;
        const __nv_bfloat16* xn = g_xn + tok * DM + lane * 4;
        const __half* xnp = g_xnp + tok * DM;
        float f[5][4], sum = 0, sq = 0, r = 0;
#pragma unroll
        for (int i = 0; i < 5; i++) {
            const uint2 v = lds64(rows + (n + 1) * 1280 + lane * 8 + i * 256);
            f[i][0] = bflo(v.x); f[i][1] = bfhi(v.x); f[i][2] = bflo(v.y); f[i][3] = bfhi(v.y);
            sum += (f[i][0] + f[i][1]) + (f[i][2] + f[i][3]);
        }
        const float mean = warp_sum(sum) * (1.0f / DM);
#pragma unroll
        for (int i = 0; i < 5; i++)
#pragma unroll
            for (int e = 0; e < 4; e++) sq = fmaf(f[i][e] - mean, f[i][e] - mean, sq);
        sq = warp_sum(sq);
        float sd, isd;
        asm("sqrt.approx.f32 %0, %1;" : "=f"(sd) : "f"(bf16_round(bf16_round(sq * (1.0f / DM)) + 1e-5f)));
        asm("rcp.approx.f32 %0, %1;" : "=f"(isd) : "f"(bf16_round(sd)));
        const float mb = bf16_round(mean);
        nmax = real ? fmaxf(nmax, fmaf((mean - mb) * (mean - mb), (float)DM, sq) * isd * isd) : 0.0f;
#pragma unroll
        for (int i = 0; i < 5; i++) {
            const uint2 w = lds64(rows + lane * 8 + i * 256);
            const uint32_t d0 = pack_bf16(f[i][0] - mb, f[i][1] - mb), d1 = pack_bf16(f[i][2] - mb, f[i][3] - mb);
            const uint32_t y0 = pack_bf16(bflo(d0) * isd, bfhi(d0) * isd), y1 = pack_bf16(bflo(d1) * isd, bfhi(d1) * isd);
            stg64_if(xn + i * 128, y0, y1, real);
            r = fmaf(bflo(y0), bflo(w.x), fmaf(bfhi(y0), bfhi(w.x), fmaf(bflo(y1), bflo(w.y), fmaf(bfhi(y1), bfhi(w.y), r))));
            const uint32_t o = __shfl_xor_sync(~0u, up ? y0 : y1, 2), lo = up ? o : y0, hi = up ? y1 : o;
            uint32_t h0, h1;
            asm("cvt.rn.satfinite.f16x2.f32 %0, %1, %2;" : "=r"(h0) : "f"(bflo(hi)), "f"(bflo(lo)));
            asm("cvt.rn.satfinite.f16x2.f32 %0, %1, %2;" : "=r"(h1) : "f"(bfhi(hi)), "f"(bfhi(lo)));
            stg64_if(xnp + slot[i], h0, h1, real);
        }
        r = warp_sum(r);
        if (lane == 0 && real) g_r[tok] = bf16_round(r);
        if (n == 0) { __syncwarp(); mbar_arrive_if(sb + MB_L0, lane == 0); }
    }
    __syncwarp();
    if (lane == 0) {
        atomicMax(fl + F_XN, __float_as_uint(sqrtf(nmax) * 1.02f));
        mbar_arrive(sb + MB_L0 + 8);
    }
}

__global__ void __cluster_dims__(3, 1, 1) __launch_bounds__(384, 1)
chain_kernel(const __grid_constant__ Maps maps, const __grid_constant__ Ptrs P) {
    extern __shared__ __align__(1024) unsigned char smem[];
    const uint32_t sb = smem_u32(smem);
    const int warp = threadIdx.x >> 5;
    if (threadIdx.x == 32) GT(0);
    if (TRIG == 0) asm volatile("griddepcontrol.launch_dependents;");
    if (threadIdx.x == 0) {
        spin_guard(mapa(sb, 0) == SM_BASE && mapa(sb, 1) == SM_BASE + SM_RANK && mapa(sb, 2) == SM_BASE + 2 * SM_RANK && sb == SM_BASE + blockIdx.x % 3 * SM_RANK ? 0 : ~0u);
        mbar_init(sb + MB_S, 1); mbar_init(sb + MB_V, 1); mbar_init(sb + MB_VX, 1); mbar_init(sb + MB_R, 1); mbar_init(sb + MB_RDY, 2);
        mbar_init(sb + MB_PUB, 4); mbar_init(sb + MB_PUB + 8, 4);
        mbar_init(sb + MB_XN, 1); mbar_init(sb + MB_XNF, 8); mbar_init(sb + MB_KT, 4); mbar_init(sb + MB_KTF, 1);
        mbar_init(sb + MB_AT, 1); mbar_init(sb + MB_AT + 8, 1);
        for (int i = 0; i < 8; i++) mbar_init(sb + MB_KM + i * 8, 1);
        mbar_init(sb + MB_GO, 8); mbar_init(sb + MB_OM, 8); mbar_init(sb + MB_MEM, 8); mbar_init(sb + MB_XN2, 1); mbar_init(sb + MB_CST, 1);
        for (int i = 0; i < 8; i++) mbar_init(sb + MB_PF + i * 8, 1);
        for (int i = 0; i < 3; i++) mbar_init(sb + MB_PE + i * 8, 4);
        for (int i = 0; i < 5; i++) mbar_init(sb + MB_PO + i * 8, 1);
        sts64(sb + SM_CST + 40, 0, 0); sts64(sb + SM_CST + 48, 0, 0); sts64(sb + SM_CST + 56, 0, 0); sts128(sb + SM_AD, 0, 0, 0, 0);
        for (int i = 0; i < 8; i++) mbar_init(sb + MB_LN + i * 8, 1);
        mbar_init(sb + MB_L0, 8); mbar_init(sb + MB_L0 + 8, 8);
        uint32_t smid; asm volatile("mov.u32 %0, %%smid;" : "=r"(smid));
        sts32(sb + SM_RV, SM_BASE + (ROLE_SWAP ? smid & 1 : 1) * 2 * SM_RANK);
        asm volatile("fence.mbarrier_init.release.cluster;" ::: "memory");
    }
    __syncthreads();
    asm volatile("barrier.cluster.arrive.release.aligned; barrier.cluster.wait.acquire.aligned;" ::: "memory");
    uint32_t rv;
    asm volatile("ld.volatile.shared::cluster.u32 %0, [%1];" : "=r"(rv) : "r"(P.sb0 + SM_RANK + SM_RV) : "memory");
    if (warp < 8) layernorm_rows(P, sb, blockIdx.x * 8 + warp, threadIdx.x & 31);
    if (TRIG == 1 && warp == 0) asm volatile("griddepcontrol.launch_dependents;");
    sts32(sb + SM_RV + 4, rv);
    if (V_FIRST ? __all_sync(~0u, rv != sb) : !__any_sync(~0u, rv == sb)) {
        if (warp < 8) {
            asm volatile("setmaxnreg.inc.sync.aligned.u32 240;");
            const int cta = cta_now(), h = cta / 3, j = (cta - 3 * h) & 1;
            chain_main(sb, h, j, warp, tid_now() & 31, P);
            asm volatile("barrier.cluster.arrive.release.aligned; barrier.cluster.wait.acquire.aligned;" ::: "memory");
        } else {
            asm volatile("setmaxnreg.dec.sync.aligned.u32 24;");
            const int cta = cta_now(), h = cta / 3, j = (cta - 3 * h) & 1;
            chain_aux<false>(sb, 2 * h + j, h, j, warp - 8, tid_now() & 31, &maps, &P);
        }
    } else {
        if (warp < 8) {
            asm volatile("setmaxnreg.inc.sync.aligned.u32 %0;" :: "n"(VS_REGS));
            const int h = cta_now() / 3;
            vs_main(sb, h, warp, tid_now() & 31, P, &maps);
            asm volatile("barrier.cluster.arrive.release.aligned; barrier.cluster.wait.acquire.aligned;" ::: "memory");
        } else {
            asm volatile("setmaxnreg.dec.sync.aligned.u32 %0;" :: "n"(504 - 2 * VS_REGS));
            const int h = cta_now() / 3;
            chain_aux<true>(sb, h, h, 0, warp - 8, tid_now() & 31, &maps, &P);
        }
    }
}

__global__ void __launch_bounds__(384, 1)
gemm_kernel(const __grid_constant__ Maps maps, const __grid_constant__ Ptrs P) {
    extern __shared__ __align__(1024) unsigned char smem[];
    const uint32_t sb = P.sb0;
    const int warp = threadIdx.x >> 5;
    if (threadIdx.x == 0) {
        spin_guard(smem_u32(smem) == SM_BASE ? 0 : ~0u);
        for (int i = 0; i < 4; i++) { mbar_init(sb + GB_QF + i * 8, 1); mbar_init(sb + GB_QE + i * 8, 8); }
        for (int i = 0; i < 8; i++) { mbar_init(sb + GB_OF + i * 8, 1); mbar_init(sb + GB_OE + i * 8, 4); }
        mbar_init(sb + GB_ML, 1);
        mbar_init(sb + GB_WO, 1); mbar_init(sb + GB_QD, 1);
        for (int i = 0; i < 8; i++) mbar_init(sb + MB_LN + i * 8, 1);
        asm volatile("fence.mbarrier_init.release.cluster;" ::: "memory");
    }
    if (threadIdx.x >= 32 && threadIdx.x < 32 + GD_O + 32) mbar_init(sb + GB_DONE + (threadIdx.x - 32) * 8, threadIdx.x < 32 + GD_O ? 8 : 4);
    __syncthreads();
    if (threadIdx.x == 0) GT(0);
    if (warp < 8) {
        asm volatile("setmaxnreg.inc.sync.aligned.u32 240;");
        gemm_main(smem, sb, cta_now(), tid_now(), P);
    } else {
        asm volatile("setmaxnreg.dec.sync.aligned.u32 24;");
        const int lane = tid_now() & 31, cta = cta_now();
        if (warp == 11) gemm_publisher(sb, cta, lane);
        else {
            gemm_producer_q(sb, cta, __reduce_max_sync(~0u, warp) - 8, lane, &maps);
            if (tid_now() == 256) gemm_producer(sb, cta_now(), &maps);
            __syncwarp();
            gemm_producer_o(sb, cta_now(), __reduce_max_sync(~0u, tid_now() >> 5) - 8, tid_now() & 31, P.x);
        }
    }
}

typedef CUresult (*EncodeTiledFn)(CUtensorMap*, CUtensorMapDataType, cuuint32_t, void*, const cuuint64_t*, const cuuint64_t*, const cuuint32_t*,
                                  const cuuint32_t*, CUtensorMapInterleave, CUtensorMapSwizzle, CUtensorMapL2promotion, CUtensorMapFloatOOBfill);
static void make_map(EncodeTiledFn fn, CUtensorMap* m, const void* p, uint64_t cols, uint64_t rows, uint32_t bc, uint32_t br) {
    cuuint64_t dims[2] = {cols, rows}, strides[1] = {cols * 2};
    cuuint32_t box[2] = {bc, br}, es[2] = {1, 1};
    fn(m, CU_TENSOR_MAP_DATA_TYPE_BFLOAT16, 2, const_cast<void*>(p), dims, strides, box, es, CU_TENSOR_MAP_INTERLEAVE_NONE,
       CU_TENSOR_MAP_SWIZZLE_128B, CU_TENSOR_MAP_L2_PROMOTION_L2_256B, CU_TENSOR_MAP_FLOAT_OOB_FILL_NONE);
}

extern "C" void kernel_launch(void* const* d_in, const int* in_sizes, int n_in, void* d_out, int out_size) {
    typedef const __nv_bfloat16* bp;
    void* fp = nullptr; cudaDriverEntryPointQueryResult qr;
    cudaGetDriverEntryPoint("cuTensorMapEncodeTiled", &fp, cudaEnableDefault, &qr);
    EncodeTiledFn enc = (EncodeTiledFn)fp;
    void *xn, *xnp;
    cudaGetSymbolAddress(&xn, g_xn); cudaGetSymbolAddress(&xnp, g_xnp);
    Maps maps;
    make_map(enc, &maps.q, d_in[2], HD, DM, 64, 160); make_map(enc, &maps.k, d_in[3], HD, DM, 64, 160);
    make_map(enc, &maps.v, d_in[4], HD, DM, 64, 160); make_map(enc, &maps.o, d_in[5], DM, HD, 64, 128);
    {
        cuuint64_t dims[3] = {64, S_TOK, 10}, strides[2] = {DM * 2, 128};
        cuuint32_t box[3] = {64, 32, 10}, es[3] = {1, 1, 1};
        enc(&maps.xnp, CU_TENSOR_MAP_DATA_TYPE_BFLOAT16, 3, xnp, dims, strides, box, es, CU_TENSOR_MAP_INTERLEAVE_NONE,
            CU_TENSOR_MAP_SWIZZLE_128B, CU_TENSOR_MAP_L2_PROMOTION_L2_256B, CU_TENSOR_MAP_FLOAT_OOB_FILL_NONE);
    }
    make_map(enc, &maps.xn, xn, DM, S_TOK, 64, 128);
    {
        cuuint64_t dims[3] = {64, DM, HD / 64}, strides[2] = {HD * 2, 128};
        cuuint32_t box[3] = {64, 64, 4}, es[3] = {1, 1, 1};
        enc(&maps.q64, CU_TENSOR_MAP_DATA_TYPE_BFLOAT16, 3, d_in[2], dims, strides, box, es, CU_TENSOR_MAP_INTERLEAVE_NONE,
            CU_TENSOR_MAP_SWIZZLE_128B, CU_TENSOR_MAP_L2_PROMOTION_L2_256B, CU_TENSOR_MAP_FLOAT_OOB_FILL_NONE);
    }
    make_map(enc, &maps.o64, d_in[5], DM, HD, 64, 64);
    make_map(enc, &maps.wg, d_in[9], FF, DM, 64, 160); make_map(enc, &maps.wu, d_in[10], FF, DM, 64, 160); make_map(enc, &maps.wd, d_in[11], DM, FF, 64, 64);
    Ptrs P = {(bp)d_in[0], (bp)d_in[1], (bp)d_in[8], (bp)d_in[2], (bp)d_in[3], (bp)d_in[4], (bp)d_in[5], (__nv_bfloat16*)d_out, 0, (uint64_t)WG_DESC_HI << 32 | 1u << 16, (uint64_t)WG_DESC_HI << 32 | (8192u >> 4) << 16, (uint64_t)(1024u >> 4) << 32 | (128u >> 4) << 16, SM_BASE, SM_BASE + 2 * SM_RANK};
    cudaFuncSetAttribute(chain_kernel, cudaFuncAttributeMaxDynamicSharedMemorySize, CHAIN_SMEM);
    cudaFuncSetAttribute(gemm_kernel, cudaFuncAttributeMaxDynamicSharedMemorySize, CHAIN_SMEM);
    chain_kernel<<<96, 384, CHAIN_SMEM>>>(maps, P);
    cudaLaunchConfig_t cfg = {};
    cfg.gridDim = dim3(NG); cfg.blockDim = dim3(384); cfg.dynamicSmemBytes = CHAIN_SMEM; cfg.stream = 0;
    cudaLaunchAttribute at[1];
    at[0].id = cudaLaunchAttributeProgrammaticStreamSerialization; at[0].val.programmaticStreamSerializationAllowed = 1;
    cfg.attrs = at; cfg.numAttrs = 1;
    cudaLaunchKernelEx(&cfg, gemm_kernel, maps, P);
}
```
